```python
import torch

def _softmax(x, axis=-1):
    return torch.softmax(x, dim=axis)

def _gelu(x):
    return torch.nn.functional.gelu(x, approximate='tanh')

def _silu(x):
    return torch.nn.functional.silu(x)

def _sigmoid(x):
    return torch.sigmoid(x)

def _layernorm(x, axis=-1, eps=1e-05):
    m = x.mean(dim=axis, keepdim=True)
    v = x.var(dim=axis, keepdim=True, unbiased=False)
    return (x - m) / torch.sqrt(v + eps)

def _scatter_add(tgt, idx, src, axis=0):
    return tgt.clone().index_add_(axis, idx, src)

def _segment_sum(src, seg, n):
    out = torch.zeros((n,) + src.shape[1:], dtype=src.dtype)
    return out.index_add_(0, seg, src)

def _pad(x, pw):
    flat = tuple((v for pair in reversed(pw) for v in pair))
    return torch.nn.functional.pad(x, flat)
kernel_name = 'standalone__tree_speculative_verify_tree_attention_over_candidate_token_tree__sampling'

def setup_inputs():

    _w = lambda a: (lambda t: t.to(torch.bfloat16) if t.is_floating_point() else t)(torch.as_tensor(a))
    B, Hq, Hkv, T, C, D = (16, 32, 8, 32, 4096, 128)
    tree_mask = torch.zeros((B, T, T), dtype=float)
    for b in range(B):
        parent = torch.zeros(T, dtype=torch.int64)
        for i in range(1, T):
            parent[i] = int(torch.randint(0, i, (1,)).item())
        for i in range(T):
            j = i
            tree_mask[b, i, j] = 1.0
            while j > 0:
                j = parent[j]
                tree_mask[b, i, j] = 1.0
    return {'q': _w((lambda *s: torch.randn(*s, dtype=torch.bfloat16) * 0.8)(B, Hq, T, D)), 'k_cache': _w((lambda *s: torch.randn(*s, dtype=torch.bfloat16) * 0.8)(B, Hkv, C, D)), 'v_cache': _w((lambda *s: torch.randn(*s, dtype=torch.bfloat16) * 0.05)(B, Hkv, C, D)), 'k_tree': _w((lambda *s: torch.randn(*s, dtype=torch.bfloat16) * 0.8)(B, Hkv, T, D)), 'v_tree': _w((lambda *s: torch.randn(*s, dtype=torch.bfloat16) * 0.05)(B, Hkv, T, D)), 'tree_mask': _w(tree_mask)}

def reference(q, k_cache, v_cache, k_tree, v_tree, tree_mask):
    B, Hq, T, D = q.shape
    Hkv, C = (k_cache.shape[1], k_cache.shape[2])
    rep = Hq // Hkv
    kc = (lambda x, n, axis: torch.repeat_interleave(x, n, dim=axis))(k_cache, rep, axis=1)
    vc = (lambda x, n, axis: torch.repeat_interleave(x, n, dim=axis))(v_cache, rep, axis=1)
    kt = (lambda x, n, axis: torch.repeat_interleave(x, n, dim=axis))(k_tree, rep, axis=1)
    vt = (lambda x, n, axis: torch.repeat_interleave(x, n, dim=axis))(v_tree, rep, axis=1)
    k = torch.concatenate([kc, kt], axis=2)
    v = torch.concatenate([vc, vt], axis=2)
    scale = D ** (-0.5)
    scores = torch.einsum('bhqd,bhkd->bhqk', q, k) * scale
    ctx_mask = torch.ones((B, 1, T, C), dtype=scores.dtype)
    tm = tree_mask[:, None, :, :].clone()
    full_mask = torch.concatenate([ctx_mask, tm], axis=-1)
    scores = scores + (1.0 - full_mask) * -1000000000.0
    p = _softmax(scores, axis=-1)
    return torch.einsum('bhqk,bhkd->bhqd', p, v)
```

```cpp
#include <cuda_runtime.h>
#include <cuda_bf16.h>
#include <cuda.h>
#include <stdint.h>

namespace {

constexpr int kB = 16, kHq = 32, kHkv = 8, kT = 32, kC = 4096, kD = 128;
constexpr int kCtas = kB * kHkv;
constexpr int kRows = (kHq / kHkv) * kT;
constexpr int kTile = 128;
constexpr int kTiles = kC / kTile;
constexpr int kItems = 2 * kTiles;
constexpr int kTileBytes = kTile * kD * 2;
constexpr int kStages = 5;
constexpr int kSub = 4;
constexpr int kSubBytes = kTileBytes / kSub;
constexpr int kPairEnd = 28;
constexpr int kOddXor = 7;
constexpr int kEndBars = 10;

constexpr int kUnit = 4656;
__host__ __device__ constexpr int clk(int units) { return units * kUnit / 256; }
constexpr int kWindow = 164;
constexpr int kWindowSlope = 2;
constexpr int kWindowExtra = 100;
constexpr int kStartT0 = 200;
constexpr uint32_t kPaceStart = 448;

constexpr int kOffQ = 0;
constexpr int kOffKt = 32768;
constexpr int kOffVt = kOffKt + 8192;
constexpr int kOffMask = kOffVt + 8192;
constexpr int kOffRing = kOffMask + 2048;
constexpr int kOffBar = kOffRing + kStages * kTileBytes;
constexpr int kSmemBytes = kOffBar + 512 + 1024;
constexpr int kThreads = 384;

__device__ unsigned int g_progress;

__device__ __forceinline__ uint32_t smem_u32(const void* p) { return (uint32_t)__cvta_generic_to_shared(p); }

__device__ __forceinline__ void mbar_init(uint32_t bar, uint32_t cnt) {
    asm volatile("mbarrier.init.shared::cta.b64 [%0], %1;" ::"r"(bar), "r"(cnt) : "memory");
}
__device__ __forceinline__ void mbar_expect_tx(uint32_t bar, uint32_t bytes) {
    asm volatile("mbarrier.arrive.expect_tx.shared::cta.b64 _, [%0], %1;" ::"r"(bar), "r"(bytes) : "memory");
}
__device__ __forceinline__ void mbar_arrive(uint32_t bar) {
    asm volatile("mbarrier.arrive.shared::cta.b64 _, [%0];" ::"r"(bar) : "memory");
}
__device__ __forceinline__ void mbar_wait(uint32_t bar, uint32_t parity) {
    asm volatile(
        "{\n.reg .pred p, q;\n.reg .u32 n;\nmov.u32 n, 0;\n"
        "WAIT_%=:\n"
        "mbarrier.try_wait.parity.shared::cta.b64 p, [%0], %1;\n"
        "add.u32 n, n, 1;\n"
        "setp.lt.and.u32 q, n, %2, !p;\n"
        "@q bra WAIT_%=;\n}"
        ::"r"(bar), "r"(parity), "n"(0x20000) : "memory");
}

__device__ __forceinline__ void tma_load(uint32_t dst, const CUtensorMap* m, uint32_t bar, int half, int grp) {
    asm volatile(
        "cp.async.bulk.tensor.4d.shared::cluster.global.mbarrier::complete_tx::bytes [%0], [%1, {%3, %3, %4, %5}], [%2];"
        ::"r"(dst), "l"(m), "r"(bar), "r"(0), "r"(half), "r"(grp) : "memory");
}
__device__ __forceinline__ void tma_stream(uint32_t dst, const CUtensorMap* m, uint32_t bar, int half, int grp, uint64_t pol) {
    asm volatile(
        "{\n.reg .pred p;\nelect.sync _|p, 0xffffffff;\n"
        "@p cp.async.bulk.tensor.4d.shared::cluster.global.mbarrier::complete_tx::bytes.L2::cache_hint"
        " [%0], [%1, {%3, %3, %4, %5}], [%2], %6;\n}"
        ::"r"(dst), "l"(m), "r"(bar), "r"(0), "r"(half), "r"(grp), "l"(pol) : "memory");
}
__device__ __forceinline__ void pace_wait(uint32_t slot, int due) {
    asm volatile(
        "{\n.reg .pred p;\n.reg .u32 t, c;\n"
        "PACE_%=:\n"
        "ld.volatile.shared.u32 t, [%0];\n"
        "mov.u32 c, %clock;\n"
        "sub.u32 c, c, t;\n"
        "setp.lt.s32 p, c, %1;\n"
        "@p bra.uni PACE_%=;\n}"
        ::"r"(slot), "r"(due) : "memory");
}
__device__ __forceinline__ void prefetch_map(const CUtensorMap* m) {
    asm volatile("prefetch.tensormap [%0];" ::"l"(m) : "memory");
}

__device__ __forceinline__ uint64_t make_desc(uint32_t addr, uint32_t sbo) {
    return (uint64_t)((addr & 0x3FFFF) >> 4) | (1ull << 16) | ((uint64_t)(sbo >> 4) << 32) | (1ull << 62);
}

__device__ __forceinline__ void wg_fence() { asm volatile("wgmma.fence.sync.aligned;" ::: "memory"); }
__device__ __forceinline__ void wg_commit() { asm volatile("wgmma.commit_group.sync.aligned;" ::: "memory"); }
template <int N> __device__ __forceinline__ void wg_wait() { asm volatile("wgmma.wait_group.sync.aligned %0;" ::"n"(N) : "memory"); }
template <int LO, int HI, int N> __device__ __forceinline__ void fence_regs(float (&r)[N]) {
#pragma unroll
    for (int i = LO; i < HI; i++) asm volatile("" : "+f"(r[i])::"memory");
}
__device__ __forceinline__ void bar_sync(int id) { asm volatile("barrier.sync %0, 256;" ::"r"(id) : "memory"); }
__device__ __forceinline__ void bar_arrive(int id) { asm volatile("barrier.arrive %0, 256;" ::"r"(id) : "memory"); }

#define ACC8(d, o) "+f"(d[o]), "+f"(d[o + 1]), "+f"(d[o + 2]), "+f"(d[o + 3]), "+f"(d[o + 4]), "+f"(d[o + 5]), "+f"(d[o + 6]), "+f"(d[o + 7])
#define ACC32(d, o) ACC8(d, o), ACC8(d, o + 8), ACC8(d, o + 16), ACC8(d, o + 24)
#define REGS32                                                                \
    "{%0, %1, %2, %3, %4, %5, %6, %7, %8, %9, %10, %11, %12, %13, %14, %15, " \
    "%16, %17, %18, %19, %20, %21, %22, %23, %24, %25, %26, %27, %28, %29, %30, %31}"

template <int O>
__device__ __forceinline__ void wgmma_qk64(float (&d)[64], uint64_t da, uint64_t db, int acc) {
    asm volatile(
        "{\n.reg .pred p;\nsetp.ne.b32 p, %34, 0;\n"
        "wgmma.mma_async.sync.aligned.m64n64k16.f32.bf16.bf16 " REGS32 ", %32, %33, p, 1, 1, 0, 0;\n}"
        : ACC32(d, O) : "l"(da), "l"(db), "r"(acc));
}
__device__ __forceinline__ void wgmma_qk32(float (&d)[16], uint64_t da, uint64_t db, int acc) {
    asm volatile(
        "{\n.reg .pred p;\nsetp.ne.b32 p, %18, 0;\n"
        "wgmma.mma_async.sync.aligned.m64n32k16.f32.bf16.bf16 "
        "{%0, %1, %2, %3, %4, %5, %6, %7, %8, %9, %10, %11, %12, %13, %14, %15}, %16, %17, p, 1, 1, 0, 0;\n}"
        : ACC8(d, 0), ACC8(d, 8) : "l"(da), "l"(db), "r"(acc));
}
template <int O>
__device__ __forceinline__ void wgmma_pv64(float (&d)[64], const uint32_t* a, uint64_t db) {
    asm volatile(
        "{\n.reg .pred p;\nsetp.ne.b32 p, 1, 0;\n"
        "wgmma.mma_async.sync.aligned.m64n64k16.f32.bf16.bf16 " REGS32 ", {%32, %33, %34, %35}, %36, p, 1, 1, 1;\n}"
        : ACC32(d, O) : "r"(a[0]), "r"(a[1]), "r"(a[2]), "r"(a[3]), "l"(db));
}
__device__ __forceinline__ void pv_piece(float (&o)[64], const uint32_t* a, uint64_t dv) {
    wg_fence();
    wgmma_pv64<0>(o, a, dv);
    wgmma_pv64<0>(o, a + 4, dv + (4096 >> 4));
    wg_commit();
    wgmma_pv64<32>(o, a, dv + (1024 >> 4));
    wgmma_pv64<32>(o, a + 4, dv + (5120 >> 4));
    wg_commit();
}
template <int H, int N>
__device__ __forceinline__ void pv_half_piece(float (&o)[64], const uint32_t* a, uint64_t dv) {
    wg_fence();
#pragma unroll
    for (int k = 0; k < N; k++) wgmma_pv64<32 * H>(o, a + 4 * k, dv + ((k * 2048) >> 4));
    wg_commit();
}

__device__ __forceinline__ float ex2(float x) {
    float y;
    asm("ex2.approx.ftz.f32 %0, %1;" : "=f"(y) : "f"(x));
    return y;
}
__device__ __forceinline__ float rcp(float x) {
    float y;
    asm("rcp.approx.ftz.f32 %0, %1;" : "=f"(y) : "f"(x));
    return y;
}
__device__ __forceinline__ uint32_t pack_bf16(float lo, float hi) {
    uint32_t r;
    asm("cvt.rn.bf16x2.f32 %0, %1, %2;" : "=r"(r) : "f"(hi), "f"(lo));
    return r;
}
__device__ __forceinline__ float quad_max(float x) {
    x = fmaxf(x, __shfl_xor_sync(0xffffffffu, x, 1));
    return fmaxf(x, __shfl_xor_sync(0xffffffffu, x, 2));
}
__device__ __forceinline__ float quad_sum(float x) {
    x += __shfl_xor_sync(0xffffffffu, x, 1);
    return x + __shfl_xor_sync(0xffffffffu, x, 2);
}

struct Ring {
    int s;
    uint32_t ph;
    __device__ __forceinline__ void next() { if (++s == kStages) { s = 0; ph ^= 1; } }
};

__device__ __forceinline__ bool item_is_v(int i) {
    return i < 2 * kPairEnd ? (i & 2) != 0 : i >= kItems - 4 ? i != kItems - 4 : (i > 2 * kPairEnd && !(i & 1));
}
__device__ __forceinline__ int item_tile(int i) {
    return i < 2 * kPairEnd ? (i >> 2) * 2 + (i & 1) : i == kItems - 4 ? kTiles - 1 : item_is_v(i) ? (i >> 1) - 1 : (i + 1) >> 1;
}
__host__ __device__ constexpr int end_pos(int x) { return x < 6 ? 2 * x : 6 + x; }
__host__ __device__ constexpr int end_off(int x) {
    return kOffRing + (kItems - 2 + end_pos(x) / 8) % kStages * kTileBytes + end_pos(x) % 8 * 4096;
}

__global__ void __launch_bounds__(kThreads, 1)
tree_attn_kernel(const __nv_bfloat16* __restrict__ q,
                 const __grid_constant__ CUtensorMap tmQ, const __grid_constant__ CUtensorMap tmK,
                 const __grid_constant__ CUtensorMap tmKt, const __grid_constant__ CUtensorMap tmVt,
                 const __grid_constant__ CUtensorMap tmV, const __grid_constant__ CUtensorMap tmVl,
                 const __grid_constant__ CUtensorMap tmVr, const __grid_constant__ CUtensorMap tmO,
                 const __nv_bfloat16* __restrict__ mask, __nv_bfloat16* __restrict__ out) {
    extern __shared__ uint8_t smem_raw[];
    if (threadIdx.x == 0)
        asm volatile("cp.async.bulk.prefetch.L2.global [%0], 32768;" ::"l"(q + (size_t)blockIdx.x * kRows * kD));
    const uint32_t sb = (smem_u32(smem_raw) + 1023u) & ~1023u;
    const uint32_t bar_q = sb + kOffBar;
    const uint32_t bar_empty = bar_q + 8;
    const uint32_t bar_full = bar_empty + 8 * kStages;
    const uint32_t bar_end = bar_full + 8 * kStages * kSub;
    const uint32_t pace_slot = sb + kOffBar + 448;
    const uint32_t done_flag = pace_slot + 4;
    static_assert(8 * (1 + kStages + kStages * kSub + kEndBars) <= 448, "barrier area");
    const int cta = blockIdx.x;

    if (threadIdx.x == 256) {
        mbar_init(bar_q, 1);
        asm volatile("fence.mbarrier_init.release.cluster;" ::: "memory");
        mbar_expect_tx(bar_q, 32768 + 16384 + 2048);
        tma_load(sb + kOffQ, &tmQ, bar_q, 0, cta * (kRows / 8));
        tma_load(sb + kOffKt, &tmKt, bar_q, 0, cta * (kT / 8));
        tma_load(sb + kOffVt, &tmVt, bar_q, 0, cta * (kT / 8));
        asm volatile("cp.async.bulk.shared::cluster.global.mbarrier::complete_tx::bytes [%0], [%1], 2048, [%2];"
                     ::"r"(sb + kOffMask), "l"(mask + (cta / kHkv) * kT * kT), "r"(bar_q) : "memory");
#pragma unroll
        for (int i = 0; i < kStages; i++) mbar_init(bar_empty + 8 * i, 9);
#pragma unroll
        for (int i = 0; i < kStages * kSub + kEndBars; i++) mbar_init(bar_full + 8 * i, 1);
        asm volatile("st.shared.v4.u32 [%0], {%1, %2, %2, %2};"
                     ::"r"(pace_slot), "r"((uint32_t)clock() + (kStartT0 + clk(kWindow + kWindowExtra))), "r"(0) : "memory");
        asm volatile("fence.mbarrier_init.release.cluster;" ::: "memory");
    }
    __syncwarp();
    const int warp = __shfl_sync(0xffffffffu, threadIdx.x >> 5, 0);
    const int lane = threadIdx.x & 31;

    if (warp >= 8) {
        asm volatile("setmaxnreg.dec.sync.aligned.u32 40;");
        if (warp == 8) {
            asm volatile("barrier.arrive 7, 352;" ::: "memory");
            uint64_t pol;
            asm volatile("createpolicy.fractional.L2::evict_first.b64 %0, 1.0;" : "=l"(pol));
            if (lane < kEndBars) mbar_expect_tx(bar_end + 8 * lane, lane < 6 ? kSubBytes : kSubBytes / 2);
            Ring r{0, 1};
            const int g0 = cta * (kC / 8), gx = (cta & 1) * kOddXor * 8;
            int due = -clk(kWindow), extra = (kItems * kSub - 1) * clk(kWindowSlope);
#pragma unroll 1
            for (int i = 0; i < kItems - 2; i++) {
                const bool isv = item_is_v(i);
                const CUtensorMap* tm = isv ? &tmV : &tmK;
                const uint32_t bar = bar_full + 8 * (r.s * kSub), dst = sb + kOffRing + r.s * kTileBytes;
                const int grp = item_tile(i) * (kTile / 8);
                mbar_wait(bar_empty + 8 * r.s, r.ph);
                if (lane < kSub) mbar_expect_tx(bar + 8 * lane, isv ? kSubBytes : (lane & 1) ? 0 : 2 * kSubBytes);
                __syncwarp();
#pragma unroll
                for (int u = 0; u < kSub; u++) {
                    pace_wait(pace_slot, due - min(clk(kWindowExtra), extra));
                    tma_stream(dst + u * kSubBytes, tm, bar + 8 * (isv ? u : u & 2), 0, g0 + ((grp + 4 * u) ^ gx), pol);
                    due += clk(kCtas / kSub);
                    extra -= clk(kWindowSlope);
                }
                r.next();
            }
#pragma unroll
            for (int x = 0; x < kEndBars; x++) {
                if (end_pos(x) % 8 == 0) {
                    mbar_wait(bar_empty + 8 * r.s, r.ph);
                    r.next();
                }
                pace_wait(pace_slot, due + clk(16 * end_pos(x) - (x < 6 ? 0 : 8)) - (7 - end_pos(x) / 2) * clk(kWindowSlope));
                const int grp = (kTiles - 2) * (kTile / 8) + (x < 2 ? 8 * x : x < 6 ? 8 + 4 * x : 4 * (x - 6));
                tma_stream(sb + end_off(x), x < 2 ? &tmVl : x < 6 ? &tmV : &tmVr, bar_end + 8 * x, x >= 6, g0 + (grp ^ gx), pol);
            }
            if (lane == 0) asm volatile("st.volatile.shared.u32 [%0], %1;" ::"r"(done_flag), "r"(1) : "memory");
        } else if (warp == 9) {
            if (lane == 0) {
                prefetch_map(&tmK);
                prefetch_map(&tmV);
                prefetch_map(&tmVl);
                prefetch_map(&tmVr);
                prefetch_map(&tmO);
            }
            __syncwarp();
            asm volatile("barrier.sync 7, 352;" ::: "memory");
            if (lane == 0) {
                uint32_t org = 0, g_seen = 0, t_seen = clock();
                while (true) {
                    uint32_t g, done;
                    const uint32_t t = clock();
                    asm volatile("ld.relaxed.gpu.global.u32 %0, [%1];" : "=r"(g) : "l"(&g_progress) : "memory");
                    if (g < g_seen) break;
                    if (g > g_seen) t_seen = t;
                    g_seen = g;
                    const uint32_t x = t - ((g * kUnit) >> 8);
                    org = g < 3 * kCtas ? x : org + ((int)(x - org) >> 2);
                    if (t - t_seen > 60000u) {
                        asm volatile("st.volatile.shared.u32 [%0], %1;" ::"r"(pace_slot), "r"(t - 0x400000u) : "memory");
                        break;
                    }
                    if (g >= kPaceStart) asm volatile("st.volatile.shared.u32 [%0], %1;" ::"r"(pace_slot), "r"(org) : "memory");
                    asm volatile("ld.volatile.shared.u32 %0, [%1];" : "=r"(done) : "r"(done_flag) : "memory");
                    if (done) break;
                }
            }
        } else if (warp == 10) {
            asm volatile("barrier.sync 7, 352;" ::: "memory");
            if (lane == 0) {
                Ring r{0, 0};
#pragma unroll 1
                for (int i = 0; i < kItems - 1; i++) {
                    const bool isv = item_is_v(i);
                    if (i == kItems - 2) mbar_wait(bar_end + 8 * 3, 0);
                    else mbar_wait(bar_full + 8 * (r.s * kSub + (isv ? 3 : 2)), r.ph);
                    asm volatile("red.relaxed.gpu.global.inc.u32 [%0], %1;" ::"l"(&g_progress), "n"(kCtas * (kItems - 1) - 1) : "memory");
                    if (!isv) {
                        mbar_wait(bar_full + 8 * (r.s * kSub + 1), r.ph);
                        mbar_wait(bar_full + 8 * (r.s * kSub + 3), r.ph);
                    }
                    mbar_arrive(bar_empty + 8 * r.s);
                    r.next();
                }
            }
        }
        if (warp & 1) {
            __syncwarp();
            const int g = warp != 9;
            asm volatile("barrier.sync %0, 160;" ::"r"(5 + g) : "memory");
            asm volatile("fence.proxy.async.shared::cta;\n"
                         "{\n.reg .pred p;\nelect.sync _|p, 0xffffffff;\n"
                         "@p cp.async.bulk.tensor.4d.global.shared::cta.bulk_group [%0, {%2, %2, %2, %3}], [%1];\n"
                         "@p cp.async.bulk.commit_group;\n@p cp.async.bulk.wait_group.read 0;\n}"
                         ::"l"(&tmO), "r"(sb + kOffQ + g * 16384), "r"(0), "r"(cta * (kRows / 8) + g * 8) : "memory");
        }
    } else {
        asm volatile("setmaxnreg.inc.sync.aligned.u32 232;");
        const int wg = warp >> 2;
        const float kScale = 0.08838834764831845f;
        const float kLog2e = 1.4426950408889634f;
        const float c = kScale * kLog2e;
        if (wg == 1) {
            bar_arrive(1);
            bar_arrive(3);
        }

        const uint64_t db = make_desc(sb, 2048);
        const uint64_t dq = db + ((kOffQ + wg * 16384) >> 4);
        float o[64], sc[64];
        uint32_t p[96];
        float l0, l1, a0 = 1.f, a1 = 1.f, b0 = 1.f, b1 = 1.f;
        bool moved = false;
        Ring r{0, 0};
        float m0, m1;
#pragma unroll
        for (int i = 0; i < 64; i++) o[i] = sc[i] = 0.f, p[i] = 0;
        asm volatile("barrier.sync 7, 352;" ::: "memory");
        mbar_wait(bar_q, 0);
        {
            float st[16];
            const uint64_t dk = db + (kOffKt >> 4);
            wg_fence();
#pragma unroll
            for (int k = 0; k < 8; k++) {
                const uint32_t off = ((k >> 2) * 1024 + (k & 3) * 32) >> 4;
                wgmma_qk32(st, dq + off, dk + off, k != 0);
            }
            wg_commit();
            wg_wait<0>();
            fence_regs<0, 16>(st);
#pragma unroll
            for (int i = 0; i < 4; i++) {
#pragma unroll
                for (int h = 0; h < 2; h++) {
                    uint32_t w;
                    asm volatile("ld.shared.u32 %0, [%1];" : "=r"(w)
                                 : "r"(sb + kOffMask + ((warp & 1) * 16 + (lane >> 2) + 8 * h) * 64 + 16 * i + 4 * (lane & 3)));
                    const float ma = __uint_as_float(w << 16), mb = __uint_as_float(w & 0xffff0000u);
                    st[4 * i + 2 * h] = (st[4 * i + 2 * h] * kScale + (1.0f - ma) * -1.0e9f) * kLog2e;
                    st[4 * i + 2 * h + 1] = (st[4 * i + 2 * h + 1] * kScale + (1.0f - mb) * -1.0e9f) * kLog2e;
                }
            }
            m0 = fmaxf(st[0], st[1]);
            m1 = fmaxf(st[2], st[3]);
#pragma unroll
            for (int i = 1; i < 4; i++) {
                m0 = fmaxf(m0, fmaxf(st[4 * i], st[4 * i + 1]));
                m1 = fmaxf(m1, fmaxf(st[4 * i + 2], st[4 * i + 3]));
            }
            m0 = quad_max(m0);
            m1 = quad_max(m1);
            l0 = 0.f;
            l1 = 0.f;
#pragma unroll
            for (int i = 0; i < 4; i++) {
                const float a = ex2(st[4 * i] - m0), b = ex2(st[4 * i + 1] - m0);
                const float e = ex2(st[4 * i + 2] - m1), f = ex2(st[4 * i + 3] - m1);
                l0 += a + b;
                l1 += e + f;
                p[2 * i] = pack_bf16(a, b);
                p[2 * i + 1] = pack_bf16(e, f);
            }
        }
        bool pending = true;
#pragma unroll 1
        for (int kt = 0;;) {
            const bool pv_only = pending && kt > 0 && !(kt & 1) && kt <= kPairEnd;
            const bool tree = kt == 0;
            const bool hand_over = wg == 0 || kt < kTiles - 1;
            if (!pv_only) {
                const uint64_t dk = db + (kOffRing >> 4) + r.s * (kTileBytes >> 4);
                mbar_wait(bar_full + 8 * (r.s * kSub), r.ph);
                wg_fence();
#pragma unroll
                for (int k = 0; k < 8; k++) {
                    const uint32_t off = ((k >> 2) * 1024 + (k & 3) * 32) >> 4;
                    wgmma_qk64<0>(sc, dq + off, dk + off, k != 0);
                }
                wg_commit();
                mbar_wait(bar_full + 8 * (r.s * kSub + 2), r.ph);
                bar_sync(1 + wg);
                wg_fence();
#pragma unroll
                for (int k = 0; k < 8; k++) {
                    const uint32_t off = ((k >> 2) * 1024 + (k & 3) * 32) >> 4;
                    wgmma_qk64<32>(sc, dq + off, dk + (16384 >> 4) + off, k != 0);
                }
                wg_commit();
                if (hand_over) bar_arrive(2 - wg);
                wg_wait<1>();
                fence_regs<0, 32>(sc);
                float x0 = fmaxf(sc[0], sc[1]), x1 = fmaxf(sc[2], sc[3]);
#pragma unroll
                for (int i = 1; i < 8; i++) {
                    x0 = fmaxf(x0, fmaxf(sc[4 * i], sc[4 * i + 1]));
                    x1 = fmaxf(x1, fmaxf(sc[4 * i + 2], sc[4 * i + 3]));
                }
                asm volatile("" : "+f"(x0), "+f"(x1)::"memory");
                wg_wait<0>();
                fence_regs<32, 64>(sc);
                if (lane == 0) mbar_arrive(bar_empty + 8 * r.s);
                r.next();

#pragma unroll
                for (int i = 8; i < 16; i++) {
                    x0 = fmaxf(x0, fmaxf(sc[4 * i], sc[4 * i + 1]));
                    x1 = fmaxf(x1, fmaxf(sc[4 * i + 2], sc[4 * i + 3]));
                }
                float n0 = fmaxf(m0, quad_max(x0) * c), n1 = fmaxf(m1, quad_max(x1) * c);
                moved = __any_sync(0xffffffffu, n0 > m0 || n1 > m1);
                {
                    float z;
                    asm volatile("st.volatile.shared.f32 [%2 + 4], %3;\n"
                                 "barrier.sync %1, 256;\nld.volatile.shared.f32 %0, [%2];"
                                 : "=f"(z) : "r"(3 + wg), "r"(pace_slot + 8), "f"(n0 + n1) : "memory");
                    n0 += z;
                    n1 += z;
                }
                a0 = ex2(m0 - n0);
                a1 = ex2(m1 - n1);
                m0 = n0;
                m1 = n1;
                l0 *= a0;
                l1 *= a1;
#pragma unroll
                for (int i = 0; i < 16; i++) {
                    sc[4 * i] = ex2(fmaf(sc[4 * i], c, -n0));
                    sc[4 * i + 1] = ex2(fmaf(sc[4 * i + 1], c, -n0));
                    sc[4 * i + 2] = ex2(fmaf(sc[4 * i + 2], c, -n1));
                    sc[4 * i + 3] = ex2(fmaf(sc[4 * i + 3], c, -n1));
                    l0 += sc[4 * i] + sc[4 * i + 1];
                    l1 += sc[4 * i + 2] + sc[4 * i + 3];
                }
                {
                    asm volatile("st.volatile.shared.f32 [%0], %1;" ::"r"(pace_slot + 12), "f"(sc[59]) : "memory");
                    if (hand_over) bar_arrive(4 - wg);
                }
                if (++kt == kTiles) break;
                if (kt == kTiles - 1) {
                    b0 = a0;
                    b1 = a1;
#pragma unroll
                    for (int i = 0; i < 16; i++) {
                        p[32 + 2 * i] = pack_bf16(sc[4 * i], sc[4 * i + 1]);
                        p[32 + 2 * i + 1] = pack_bf16(sc[4 * i + 2], sc[4 * i + 3]);
                    }
                    continue;
                }
            }

            if (pending) {
                const uint64_t dv = db + (kOffRing >> 4) + r.s * (kTileBytes >> 4);
                const uint32_t vbar = bar_full + 8 * (r.s * kSub);
                if (!tree) mbar_wait(vbar, r.ph);
                pv_piece(o, p, tree ? db + (kOffVt >> 4) : dv);
                if (!tree) {
#pragma unroll
                    for (int u = 1; u < 4; u++) {
                        mbar_wait(vbar + 8 * u, r.ph);
                        pv_piece(o, p + 8 * u, dv + u * (kSubBytes >> 4));
                    }
                }
            }
            wg_wait<0>();
            fence_regs<0, 64>(o);
            if (pending && !tree) {
                if (lane == 0) mbar_arrive(bar_empty + 8 * r.s);
                r.next();
            }
            pending = !pv_only;
            if (!pv_only) {
                if (moved) {
#pragma unroll
                    for (int i = 0; i < 16; i++) {
                        o[4 * i] *= a0;
                        o[4 * i + 1] *= a0;
                        o[4 * i + 2] *= a1;
                        o[4 * i + 3] *= a1;
                    }
                }
#pragma unroll
                for (int i = 0; i < 16; i++) {
                    p[2 * i] = pack_bf16(sc[4 * i], sc[4 * i + 1]);
                    p[2 * i + 1] = pack_bf16(sc[4 * i + 2], sc[4 * i + 3]);
                }
            }
        }

        {
            constexpr int it = kItems - 3;
            float i0, i1;
#pragma unroll
            for (int u = 0; u < 4; u++) {
                mbar_wait(bar_full + 8 * (it % kStages * kSub + u), it / kStages & 1);
                pv_piece(o, p + 8 * u, db + ((kOffRing + it % kStages * kTileBytes + u * kSubBytes) >> 4));
                if (u == 0) {
                    i0 = rcp(quad_sum(l0));
                    i1 = rcp(quad_sum(l1));
                    a0 *= i0;
                    a1 *= i1;
                }
#pragma unroll
                for (int i = 4 * u; i < 4 * u + 4; i++) {
                    uint32_t* q = p + 32 + 2 * i;
                    q[0] = pack_bf16(__uint_as_float(q[0] << 16) * a0, __uint_as_float(q[0] & 0xffff0000u) * a0);
                    q[1] = pack_bf16(__uint_as_float(q[1] << 16) * a1, __uint_as_float(q[1] & 0xffff0000u) * a1);
                    q[32] = pack_bf16(sc[4 * i] * i0, sc[4 * i + 1] * i0);
                    q[33] = pack_bf16(sc[4 * i + 2] * i1, sc[4 * i + 3] * i1);
                    asm volatile("" : "+r"(q[0]), "+r"(q[1]), "+r"(q[32]), "+r"(q[33])::"memory");
                }
            }
            b0 *= a0;
            b1 *= a1;
            wg_wait<0>();
            fence_regs<0, 64>(o);
#pragma unroll
            for (int i = 0; i < 16; i++) {
                o[4 * i] *= b0;
                o[4 * i + 1] *= b0;
                o[4 * i + 2] *= b1;
                o[4 * i + 3] *= b1;
            }
        }
        const uint32_t stg = sb + kOffQ + wg * 16384 + (warp & 3) * 2048;
        const uint32_t st_base = stg + (lane & 7) * 128 + (((lane >> 3) ^ (lane & 7)) << 4);
        auto stage = [&](int h, int j) {
#pragma unroll
            for (int i = 0; i < 2; i++) {
                const float* v = o + 32 * h + 16 * i + 2 * j;
                asm volatile("stmatrix.sync.aligned.m8n8.x4.shared.b16 [%0], {%1, %2, %3, %4};"
                             ::"r"((st_base ^ (i << 6)) + h * 8192 + j * 1024), "r"(pack_bf16(v[0], v[1])),
                               "r"(pack_bf16(v[4], v[5])), "r"(pack_bf16(v[8], v[9])), "r"(pack_bf16(v[12], v[13])) : "memory");
            }
        };
        uint4* gp = reinterpret_cast<uint4*>(out + (size_t)(cta * kRows + warp * 16 + (lane >> 3)) * kD + 64) + (lane & 7);
        uint32_t ld_base = stg + 8192 + (lane >> 3) * 128 + (((lane & 7) ^ (lane >> 3)) << 4);
        asm volatile("" : "+l"(gp), "+r"(ld_base)::"memory");
        const uint64_t dh = make_desc(sb, 1024);
#pragma unroll
        for (int x = 0; x < kEndBars; x++) {
            mbar_wait(bar_end + 8 * x, 0);
            if (x < 2) pv_half_piece<0, 4>(o, p + 32 + 16 * x, dh + (end_off(x) >> 4));
            else if (x < 6) pv_piece(o, p + 64 + 8 * (x - 2), db + (end_off(x) >> 4));
            else pv_half_piece<1, 2>(o, p + 32 + 8 * (x - 6), dh + (end_off(x) >> 4));
            if (x == 5) {
                wg_wait<1>();
                fence_regs<0, 32>(o);
                stage(0, 0);
                stage(0, 1);
                asm volatile("barrier.arrive %0, 160;" ::"r"(5 + wg) : "memory");
            }
        }
        wg_wait<0>();
        fence_regs<32, 64>(o);
        uint4 v[4];
#pragma unroll
        for (int j = 0; j < 2; j++) {
            stage(1, j);
            __syncwarp();
#pragma unroll
            for (int i = 2 * j; i < 2 * j + 2; i++)
                asm volatile("ld.shared.v4.u32 {%0, %1, %2, %3}, [%4];" : "=r"(v[i].x), "=r"(v[i].y), "=r"(v[i].z), "=r"(v[i].w)
                             : "r"((ld_base ^ ((i & 1) << 6)) + i * 512) : "memory");
        }
#pragma unroll
        for (int i = 0; i < 4; i++) gp[64 * i] = v[i];
    }
}

typedef CUresult (*EncodeFn)(CUtensorMap*, CUtensorMapDataType, cuuint32_t, void*, const cuuint64_t*,
                             const cuuint64_t*, const cuuint32_t*, const cuuint32_t*, CUtensorMapInterleave,
                             CUtensorMapSwizzle, CUtensorMapL2promotion, CUtensorMapFloatOOBfill);

void make_map(EncodeFn enc, CUtensorMap* m, const void* p, uint64_t rows, uint32_t box_rows, uint32_t halves) {
    const cuuint64_t dims[4] = {64, 8, 2, rows / 8};
    const cuuint64_t strides[3] = {256, 128, 2048};
    const cuuint32_t box[4] = {64, 8, halves, box_rows / 8};
    const cuuint32_t es[4] = {1, 1, 1, 1};
    enc(m, CU_TENSOR_MAP_DATA_TYPE_BFLOAT16, 4, const_cast<void*>(p), dims, strides, box, es,
        CU_TENSOR_MAP_INTERLEAVE_NONE, CU_TENSOR_MAP_SWIZZLE_128B,
        halves == 2 ? CU_TENSOR_MAP_L2_PROMOTION_L2_256B : CU_TENSOR_MAP_L2_PROMOTION_L2_128B,
        CU_TENSOR_MAP_FLOAT_OOB_FILL_NONE);
}

}

extern "C" void kernel_launch(void* const* d_in, const int* in_sizes, int n_in, void* d_out, int out_size) {
    (void)in_sizes; (void)n_in; (void)out_size;
    static EncodeFn enc = nullptr;
    if (!enc) {
        cudaDriverEntryPointQueryResult qr;
        cudaGetDriverEntryPoint("cuTensorMapEncodeTiled", (void**)&enc, cudaEnableDefault, &qr);
        cudaFuncSetAttribute(tree_attn_kernel, cudaFuncAttributeMaxDynamicSharedMemorySize, kSmemBytes);
    }
    CUtensorMap tmQ, tmK, tmKt, tmVt, tmV, tmVl, tmVr, tmO;
    make_map(enc, &tmQ, d_in[0], (uint64_t)kCtas * kRows, kRows, 2);
    make_map(enc, &tmK, d_in[1], (uint64_t)kCtas * kC, 32, 2);
    make_map(enc, &tmV, d_in[2], (uint64_t)kCtas * kC, 32, 2);
    make_map(enc, &tmVl, d_in[2], (uint64_t)kCtas * kC, 64, 1);
    make_map(enc, &tmVr, d_in[2], (uint64_t)kCtas * kC, 32, 1);
    make_map(enc, &tmKt, d_in[3], (uint64_t)kCtas * kT, kT, 2);
    make_map(enc, &tmVt, d_in[4], (uint64_t)kCtas * kT, kT, 2);
    make_map(enc, &tmO, d_out, (uint64_t)kCtas * kRows, 64, 1);
    tree_attn_kernel<<<kCtas, kThreads, kSmemBytes, cudaStreamPerThread>>>(
        (const __nv_bfloat16*)d_in[0], tmQ, tmK, tmKt, tmVt, tmV, tmVl, tmVr, tmO, (const __nv_bfloat16*)d_in[5],
        (__nv_bfloat16*)d_out);
}
```

```cpp
#include <cuda_runtime.h>
#include <cuda_bf16.h>
#include <cuda.h>
#include <stdint.h>

namespace {

constexpr int kB = 16, kHq = 32, kHkv = 8, kT = 32, kC = 4096, kD = 128;
constexpr int kCtas = kB * kHkv;
constexpr int kRows = (kHq / kHkv) * kT;
constexpr int kTile = 128;
constexpr int kTiles = kC / kTile;
constexpr int kItems = 2 * kTiles;
constexpr int kTileBytes = kTile * kD * 2;
constexpr int kStages = 5;
constexpr int kSub = 4;
constexpr int kSubBytes = kTileBytes / kSub;
constexpr int kPairEnd = 28;
constexpr int kOddXor = 7;

constexpr int kUnit = 4656;
__host__ __device__ constexpr int clk(int units) { return units * kUnit / 256; }
constexpr int kWindow = 164;
constexpr int kWindowSlope = 2;
constexpr int kWindowExtra = 100;
constexpr int kStartT0 = 200;
constexpr uint32_t kPaceStart = 448;

constexpr int kOffQ = 0;
constexpr int kOffKt = 32768;
constexpr int kOffVt = kOffKt + 8192;
constexpr int kOffMask = kOffVt + 8192;
constexpr int kOffRing = kOffMask + 2048;
constexpr int kOffBar = kOffRing + kStages * kTileBytes;
constexpr int kSmemBytes = kOffBar + 512 + 1024;
constexpr int kThreads = 384;

__device__ unsigned int g_progress;

__device__ __forceinline__ uint32_t smem_u32(const void* p) { return (uint32_t)__cvta_generic_to_shared(p); }

__device__ __forceinline__ void mbar_init(uint32_t bar, uint32_t cnt) {
    asm volatile("mbarrier.init.shared::cta.b64 [%0], %1;" ::"r"(bar), "r"(cnt) : "memory");
}
__device__ __forceinline__ void mbar_expect_tx(uint32_t bar, uint32_t bytes) {
    asm volatile("mbarrier.arrive.expect_tx.shared::cta.b64 _, [%0], %1;" ::"r"(bar), "r"(bytes) : "memory");
}
__device__ __forceinline__ void mbar_arrive(uint32_t bar) {
    asm volatile("mbarrier.arrive.shared::cta.b64 _, [%0];" ::"r"(bar) : "memory");
}
__device__ __forceinline__ void mbar_wait(uint32_t bar, uint32_t parity) {
    asm volatile(
        "{\n.reg .pred p, q;\n.reg .u32 n;\nmov.u32 n, 0;\n"
        "WAIT_%=:\n"
        "mbarrier.try_wait.parity.shared::cta.b64 p, [%0], %1;\n"
        "add.u32 n, n, 1;\n"
        "setp.lt.and.u32 q, n, %2, !p;\n"
        "@q bra WAIT_%=;\n}"
        ::"r"(bar), "r"(parity), "n"(0x20000) : "memory");
}

__device__ __forceinline__ void tma_load(uint32_t dst, const CUtensorMap* m, uint32_t bar, int half, int grp) {
    asm volatile(
        "cp.async.bulk.tensor.4d.shared::cluster.global.mbarrier::complete_tx::bytes [%0], [%1, {%3, %3, %4, %5}], [%2];"
        ::"r"(dst), "l"(m), "r"(bar), "r"(0), "r"(half), "r"(grp) : "memory");
}
__device__ __forceinline__ void tma_stream(uint32_t dst, const CUtensorMap* m, uint32_t bar, int half, int grp, uint64_t pol) {
    asm volatile(
        "{\n.reg .pred p;\nelect.sync _|p, 0xffffffff;\n"
        "@p cp.async.bulk.tensor.4d.shared::cluster.global.mbarrier::complete_tx::bytes.L2::cache_hint"
        " [%0], [%1, {%3, %3, %4, %5}], [%2], %6;\n}"
        ::"r"(dst), "l"(m), "r"(bar), "r"(0), "r"(half), "r"(grp), "l"(pol) : "memory");
}
__device__ __forceinline__ void pace_wait(uint32_t slot, int due) {
    asm volatile(
        "{\n.reg .pred p;\n.reg .u32 t, c;\n"
        "PACE_%=:\n"
        "ld.volatile.shared.u32 t, [%0];\n"
        "mov.u32 c, %clock;\n"
        "sub.u32 c, c, t;\n"
        "setp.lt.s32 p, c, %1;\n"
        "@p bra.uni PACE_%=;\n}"
        ::"r"(slot), "r"(due) : "memory");
}
__device__ __forceinline__ void prefetch_map(const CUtensorMap* m) {
    asm volatile("prefetch.tensormap [%0];" ::"l"(m) : "memory");
}

__device__ __forceinline__ uint64_t make_desc(uint32_t addr, uint32_t sbo, uint64_t swizzle) {
    return (uint64_t)((addr & 0x3FFFF) >> 4) | (1ull << 16) | ((uint64_t)(sbo >> 4) << 32) | (swizzle << 62);
}

__device__ __forceinline__ void wg_fence() { asm volatile("wgmma.fence.sync.aligned;" ::: "memory"); }
__device__ __forceinline__ void wg_commit() { asm volatile("wgmma.commit_group.sync.aligned;" ::: "memory"); }
template <int N> __device__ __forceinline__ void wg_wait() { asm volatile("wgmma.wait_group.sync.aligned %0;" ::"n"(N) : "memory"); }
template <int LO, int HI, int N> __device__ __forceinline__ void fence_regs(float (&r)[N]) {
#pragma unroll
    for (int i = LO; i < HI; i++) asm volatile("" : "+f"(r[i])::"memory");
}
__device__ __forceinline__ void bar_sync(int id) { asm volatile("barrier.sync %0, 256;" ::"r"(id) : "memory"); }
__device__ __forceinline__ void bar_arrive(int id) { asm volatile("barrier.arrive %0, 256;" ::"r"(id) : "memory"); }

#define ACC8(d, o) "+f"(d[o]), "+f"(d[o + 1]), "+f"(d[o + 2]), "+f"(d[o + 3]), "+f"(d[o + 4]), "+f"(d[o + 5]), "+f"(d[o + 6]), "+f"(d[o + 7])
#define ACC32(d, o) ACC8(d, o), ACC8(d, o + 8), ACC8(d, o + 16), ACC8(d, o + 24)
#define REGS16 "%0, %1, %2, %3, %4, %5, %6, %7, %8, %9, %10, %11, %12, %13, %14, %15"
#define REGS32 "%16, %17, %18, %19, %20, %21, %22, %23, %24, %25, %26, %27, %28, %29, %30, %31"
#define REGS64                                                                          \
    "%32, %33, %34, %35, %36, %37, %38, %39, %40, %41, %42, %43, %44, %45, %46, %47, " \
    "%48, %49, %50, %51, %52, %53, %54, %55, %56, %57, %58, %59, %60, %61, %62, %63"

template <int O>
__device__ __forceinline__ void wgmma_qk64(float (&d)[64], uint64_t da, uint64_t db, int acc) {
    asm volatile(
        "{\n.reg .pred p;\nsetp.ne.b32 p, %34, 0;\n"
        "wgmma.mma_async.sync.aligned.m64n64k16.f32.bf16.bf16 {" REGS16 ", " REGS32 "}, %32, %33, p, 1, 1, 0, 0;\n}"
        : ACC32(d, O) : "l"(da), "l"(db), "r"(acc));
}
__device__ __forceinline__ void wgmma_qk32(float (&d)[16], uint64_t da, uint64_t db, int acc) {
    asm volatile(
        "{\n.reg .pred p;\nsetp.ne.b32 p, %18, 0;\n"
        "wgmma.mma_async.sync.aligned.m64n32k16.f32.bf16.bf16 {" REGS16 "}, %16, %17, p, 1, 1, 0, 0;\n}"
        : ACC8(d, 0), ACC8(d, 8) : "l"(da), "l"(db), "r"(acc));
}
__device__ __forceinline__ void wgmma_pv(float (&d)[64], const uint32_t* a, uint64_t db) {
    asm volatile(
        "{\n.reg .pred p;\nsetp.ne.b32 p, 1, 0;\n"
        "wgmma.mma_async.sync.aligned.m64n128k16.f32.bf16.bf16 {" REGS16 ", " REGS32 ", " REGS64 "}, {%64, %65, %66, %67}, %68, p, 1, 1, 1;\n}"
        : ACC32(d, 0), ACC32(d, 32) : "r"(a[0]), "r"(a[1]), "r"(a[2]), "r"(a[3]), "l"(db));
}
__device__ __forceinline__ void wgmma_pv(float (&d)[32], const uint32_t* a, uint64_t db) {
    asm volatile(
        "{\n.reg .pred p;\nsetp.ne.b32 p, 1, 0;\n"
        "wgmma.mma_async.sync.aligned.m64n64k16.f32.bf16.bf16 {" REGS16 ", " REGS32 "}, {%32, %33, %34, %35}, %36, p, 1, 1, 1;\n}"
        : ACC32(d, 0) : "r"(a[0]), "r"(a[1]), "r"(a[2]), "r"(a[3]), "l"(db));
}
__device__ __forceinline__ void wgmma_pv(float (&d)[16], const uint32_t* a, uint64_t db) {
    asm volatile(
        "{\n.reg .pred p;\nsetp.ne.b32 p, 1, 0;\n"
        "wgmma.mma_async.sync.aligned.m64n32k16.f32.bf16.bf16 {" REGS16 "}, {%16, %17, %18, %19}, %20, p, 1, 1, 1;\n}"
        : ACC8(d, 0), ACC8(d, 8) : "r"(a[0]), "r"(a[1]), "r"(a[2]), "r"(a[3]), "l"(db));
}
__device__ __forceinline__ void pv_piece(float (&o)[64], const uint32_t* a, uint64_t dv) {
    dv += ((1024 >> 4) - 1) << 16;
    wg_fence();
    wgmma_pv(o, a, dv);
    wgmma_pv(o, a + 4, dv + (4096 >> 4));
    wg_commit();
}

__device__ __forceinline__ float ex2(float x) {
    float y;
    asm("ex2.approx.ftz.f32 %0, %1;" : "=f"(y) : "f"(x));
    return y;
}
__device__ __forceinline__ float rcp(float x) {
    float y;
    asm("rcp.approx.ftz.f32 %0, %1;" : "=f"(y) : "f"(x));
    return y;
}
__device__ __forceinline__ uint32_t pack_bf16(float lo, float hi) {
    uint32_t r;
    asm("cvt.rn.bf16x2.f32 %0, %1, %2;" : "=r"(r) : "f"(hi), "f"(lo));
    return r;
}
__device__ __forceinline__ float quad_max(float x) {
    x = fmaxf(x, __shfl_xor_sync(0xffffffffu, x, 1));
    return fmaxf(x, __shfl_xor_sync(0xffffffffu, x, 2));
}
__device__ __forceinline__ float quad_sum(float x) {
    x += __shfl_xor_sync(0xffffffffu, x, 1);
    return x + __shfl_xor_sync(0xffffffffu, x, 2);
}

template <int V> struct IntC { static constexpr int value = V; };
template <int I, int N, class Fn> __device__ __forceinline__ void static_for(Fn&& f) {
    if constexpr (I < N) {
        f(IntC<I>{});
        static_for<I + 1, N>(f);
    }
}
struct Ring {
    int s;
    uint32_t ph;
    __device__ __forceinline__ void next() { if (++s == kStages) { s = 0; ph ^= 1; } }
};

__device__ __forceinline__ bool item_is_v(int i) {
    return i < 2 * kPairEnd ? (i & 2) != 0 : i >= kItems - 4 ? i != kItems - 4 : (i > 2 * kPairEnd && !(i & 1));
}
__device__ __forceinline__ int item_tile(int i) {
    return i < 2 * kPairEnd ? (i >> 2) * 2 + (i & 1) : i == kItems - 4 ? kTiles - 1 : item_is_v(i) ? (i >> 1) - 1 : (i + 1) >> 1;
}

enum { F, L, R, A, B };
struct EndLoad { int cols, k0, nk, bar; };
constexpr int kEndLoads = 11, kEndBars = 10;
__host__ __device__ constexpr EndLoad end_load(int j) {
    constexpr EndLoad t[kEndLoads] = {{L, 0, 4, 0},  {L, 4, 4, 1}, {A, 4, 4, 1}, {L, 8, 2, 2}, {F, 10, 2, 3}, {F, 12, 2, 4},
                                      {F, 14, 2, 5}, {R, 8, 2, 6}, {R, 0, 2, 7}, {R, 2, 2, 8}, {B, 4, 4, 9}};
    return t[j];
}
constexpr int kBarHalf = 3, kBarL = 5, kBarA = 8;
__host__ __device__ constexpr int step_bytes(int cols) { return cols == F ? 4096 : cols <= R ? 2048 : 1024; }
__host__ __device__ constexpr int end_pos(int j) { return j ? end_pos(j - 1) + end_load(j - 1).nk * step_bytes(end_load(j - 1).cols) : 0; }
__host__ __device__ constexpr int bar_bytes(int x) {
    int n = 0;
    for (int j = 0; j < kEndLoads; j++) n += end_load(j).bar == x ? end_pos(j + 1) - end_pos(j) : 0;
    return n;
}
constexpr int kOffEnd = kOffRing + (kItems - 2) % kStages * kTileBytes;
static_assert((kItems - 2) % kStages + 1 < kStages && end_pos(kEndLoads) == 2 * kTileBytes, "two adjacent slots");

__global__ void __launch_bounds__(kThreads, 1)
tree_attn_kernel(const __nv_bfloat16* __restrict__ q,
                 const __grid_constant__ CUtensorMap tmQ, const __grid_constant__ CUtensorMap tmK,
                 const __grid_constant__ CUtensorMap tmKt, const __grid_constant__ CUtensorMap tmVt,
                 const __grid_constant__ CUtensorMap tmV, const __grid_constant__ CUtensorMap tmVh64,
                 const __grid_constant__ CUtensorMap tmVh32, const __grid_constant__ CUtensorMap tmVq,
                 const __grid_constant__ CUtensorMap tmOh, const __grid_constant__ CUtensorMap tmOq,
                 const __nv_bfloat16* __restrict__ mask, __nv_bfloat16* __restrict__ out) {
    extern __shared__ uint8_t smem_raw[];
    if (threadIdx.x == 0)
        asm volatile("cp.async.bulk.prefetch.L2.global [%0], 32768;" ::"l"(q + (size_t)blockIdx.x * kRows * kD));
    const uint32_t sb = (smem_u32(smem_raw) + 1023u) & ~1023u;
    const uint32_t bar_q = sb + kOffBar;
    const uint32_t bar_empty = bar_q + 8;
    const uint32_t bar_full = bar_empty + 8 * kStages;
    const uint32_t bar_end = bar_full + 8 * kStages * kSub;
    const uint32_t pace_slot = sb + kOffBar + 448;
    const uint32_t done_flag = pace_slot + 4;
    static_assert(8 * (1 + kStages + kStages * kSub + kEndBars) <= 448, "barrier area");
    const int cta = blockIdx.x;

    if (threadIdx.x == 256) {
        mbar_init(bar_q, 1);
        asm volatile("fence.mbarrier_init.release.cluster;" ::: "memory");
        mbar_expect_tx(bar_q, 32768 + 16384 + 2048);
        tma_load(sb + kOffQ, &tmQ, bar_q, 0, cta * (kRows / 8));
        tma_load(sb + kOffKt, &tmKt, bar_q, 0, cta * (kT / 8));
        tma_load(sb + kOffVt, &tmVt, bar_q, 0, cta * (kT / 8));
        asm volatile("cp.async.bulk.shared::cluster.global.mbarrier::complete_tx::bytes [%0], [%1], 2048, [%2];"
                     ::"r"(sb + kOffMask), "l"(mask + (cta / kHkv) * kT * kT), "r"(bar_q) : "memory");
#pragma unroll
        for (int i = 0; i < kStages; i++) mbar_init(bar_empty + 8 * i, 9);
#pragma unroll
        for (int i = 0; i < kStages * kSub + kEndBars; i++) mbar_init(bar_full + 8 * i, 1);
        asm volatile("st.shared.v4.u32 [%0], {%1, %2, %2, %2};"
                     ::"r"(pace_slot), "r"((uint32_t)clock() + (kStartT0 + clk(kWindow + kWindowExtra))), "r"(0) : "memory");
        asm volatile("fence.mbarrier_init.release.cluster;" ::: "memory");
    }
    __syncwarp();
    const int warp = __shfl_sync(0xffffffffu, threadIdx.x >> 5, 0);
    const int lane = threadIdx.x & 31;

    if (warp >= 8) {
        asm volatile("setmaxnreg.dec.sync.aligned.u32 40;");
        if (warp == 8) {
            asm volatile("barrier.arrive 7, 352;" ::: "memory");
            uint64_t pol;
            asm volatile("createpolicy.fractional.L2::evict_first.b64 %0, 1.0;" : "=l"(pol));
            if (lane == 0) static_for<0, kEndBars>([&](auto x) { mbar_expect_tx(bar_end + 8 * x.value, bar_bytes(x.value)); });
            __syncwarp();
            Ring r{0, 1};
            const int g0 = cta * (kC / 8), gx = (cta & 1) * kOddXor * 8;
            int due = -clk(kWindow), extra = (kItems * kSub - 1) * clk(kWindowSlope);
#pragma unroll 1
            for (int i = 0; i < kItems - 2; i++) {
                const bool isv = item_is_v(i);
                const CUtensorMap* tm = isv ? &tmV : &tmK;
                const uint32_t bar = bar_full + 8 * (r.s * kSub), dst = sb + kOffRing + r.s * kTileBytes;
                const int grp = item_tile(i) * (kTile / 8);
                mbar_wait(bar_empty + 8 * r.s, r.ph);
                if (lane < kSub) mbar_expect_tx(bar + 8 * lane, isv ? kSubBytes : (lane & 1) ? 0 : 2 * kSubBytes);
                __syncwarp();
#pragma unroll
                for (int u = 0; u < kSub; u++) {
                    pace_wait(pace_slot, due - min(clk(kWindowExtra), extra));
                    tma_stream(dst + u * kSubBytes, tm, bar + 8 * (isv ? u : u & 2), 0, g0 + ((grp + 4 * u) ^ gx), pol);
                    due += clk(kCtas / kSub);
                    extra -= clk(kWindowSlope);
                }
                r.next();
            }
            static_for<0, kEndLoads>([&](auto jc) {
                constexpr int j = jc.value;
                constexpr EndLoad e = end_load(j);
                if (end_pos(j) % kTileBytes == 0) {
                    mbar_wait(bar_empty + 8 * r.s, r.ph);
                    r.next();
                }
                if (e.cols != A) {
                    constexpr int pos = end_pos(j) + (bar_bytes(e.bar) - kSubBytes) / 2;
                    pace_wait(pace_slot, due + clk(pos / 256) - (7 * kSubBytes - pos) / 1024 * clk(kWindowSlope) / 8);
                }
                const CUtensorMap* tm = e.cols == F ? &tmV : e.cols > R ? &tmVq : e.nk == 4 ? &tmVh64 : &tmVh32;
                tma_stream(sb + kOffEnd + end_pos(j), tm, bar_end + 8 * e.bar, e.cols == F ? 0 : e.cols - 1,
                           g0 + (((kTiles - 2) * (kTile / 8) + 2 * e.k0) ^ gx), pol);
            });
            if (lane == 0) asm volatile("st.volatile.shared.u32 [%0], %1;" ::"r"(done_flag), "r"(1) : "memory");
        } else if (warp == 9) {
            if (lane == 0) {
                prefetch_map(&tmK);
                prefetch_map(&tmV);
                prefetch_map(&tmVh64);
                prefetch_map(&tmVh32);
                prefetch_map(&tmVq);
                prefetch_map(&tmOh);
                prefetch_map(&tmOq);
            }
            __syncwarp();
            asm volatile("barrier.sync 7, 352;" ::: "memory");
            if (lane == 0) {
                uint32_t org = 0, g_seen = 0, t_seen = clock();
                while (true) {
                    uint32_t g, done;
                    const uint32_t t = clock();
                    asm volatile("ld.relaxed.gpu.global.u32 %0, [%1];" : "=r"(g) : "l"(&g_progress) : "memory");
                    if (g < g_seen) break;
                    if (g > g_seen) t_seen = t;
                    g_seen = g;
                    const uint32_t x = t - ((g * kUnit) >> 8);
                    org = g < 3 * kCtas ? x : org + ((int)(x - org) >> 2);
                    if (t - t_seen > 60000u) {
                        asm volatile("st.volatile.shared.u32 [%0], %1;" ::"r"(pace_slot), "r"(t - 0x400000u) : "memory");
                        break;
                    }
                    if (g >= kPaceStart) asm volatile("st.volatile.shared.u32 [%0], %1;" ::"r"(pace_slot), "r"(org) : "memory");
                    asm volatile("ld.volatile.shared.u32 %0, [%1];" : "=r"(done) : "r"(done_flag) : "memory");
                    if (done) break;
                }
            }
        } else if (warp == 10) {
            asm volatile("barrier.sync 7, 352;" ::: "memory");
            if (lane == 0) {
                Ring r{0, 0};
#pragma unroll 1
                for (int i = 0; i < kItems - 1; i++) {
                    const bool isv = item_is_v(i);
                    if (i == kItems - 2) mbar_wait(bar_end + 8 * kBarHalf, 0);
                    else mbar_wait(bar_full + 8 * (r.s * kSub + (isv ? 3 : 2)), r.ph);
                    asm volatile("red.relaxed.gpu.global.inc.u32 [%0], %1;" ::"l"(&g_progress), "n"(kCtas * (kItems - 1) - 1) : "memory");
                    if (!isv) {
                        mbar_wait(bar_full + 8 * (r.s * kSub + 1), r.ph);
                        mbar_wait(bar_full + 8 * (r.s * kSub + 3), r.ph);
                    }
                    mbar_arrive(bar_empty + 8 * r.s);
                    r.next();
                }
            }
        }
        if (warp >= 10) {
            __syncwarp();
            const int g = 11 - warp;
#pragma unroll
            for (int i = 0; i < 2; i++)
                asm volatile("barrier.sync %0, 160;\nfence.proxy.async.shared::cta;\n"
                             "{\n.reg .pred p;\nelect.sync _|p, 0xffffffff;\n"
                             "@p cp.async.bulk.tensor.4d.global.shared::cta.bulk_group [%1, {%3, %3, %4, %5}], [%2];\n}"
                             ::"r"(5 + 3 * i + g), "l"(i ? &tmOq : &tmOh), "r"(sb + kOffQ + g * 16384 + i * 8192), "r"(0), "r"(2 * i),
                               "r"(cta * (kRows / 8) + g * 8) : "memory");
            asm volatile("cp.async.bulk.commit_group;\ncp.async.bulk.wait_group.read 0;" ::: "memory");
        }
    } else {
        asm volatile("setmaxnreg.inc.sync.aligned.u32 232;");
        const int wg = warp >> 2;
        const float kScale = 0.08838834764831845f;
        const float kLog2e = 1.4426950408889634f;
        const float c = kScale * kLog2e;
        if (wg == 1) {
            bar_arrive(1);
            bar_arrive(3);
        }

        const uint64_t db = make_desc(sb, 2048, 1);
        const uint64_t dq = db + ((kOffQ + wg * 16384) >> 4);
        float o[64], sc[64];
        uint32_t p[96];
        float l0, l1, a0 = 1.f, a1 = 1.f, b0 = 1.f, b1 = 1.f;
        bool moved = false;
        Ring r{0, 0};
        float m0, m1;
#pragma unroll
        for (int i = 0; i < 64; i++) o[i] = sc[i] = 0.f, p[i] = 0;
        asm volatile("barrier.sync 7, 352;" ::: "memory");
        mbar_wait(bar_q, 0);
        {
            float st[16];
            const uint64_t dk = db + (kOffKt >> 4);
            wg_fence();
#pragma unroll
            for (int k = 0; k < 8; k++) {
                const uint32_t off = ((k >> 2) * 1024 + (k & 3) * 32) >> 4;
                wgmma_qk32(st, dq + off, dk + off, k != 0);
            }
            wg_commit();
            wg_wait<0>();
            fence_regs<0, 16>(st);
#pragma unroll
            for (int i = 0; i < 4; i++) {
#pragma unroll
                for (int h = 0; h < 2; h++) {
                    uint32_t w;
                    asm volatile("ld.shared.u32 %0, [%1];" : "=r"(w)
                                 : "r"(sb + kOffMask + ((warp & 1) * 16 + (lane >> 2) + 8 * h) * 64 + 16 * i + 4 * (lane & 3)));
                    const float ma = __uint_as_float(w << 16), mb = __uint_as_float(w & 0xffff0000u);
                    st[4 * i + 2 * h] = (st[4 * i + 2 * h] * kScale + (1.0f - ma) * -1.0e9f) * kLog2e;
                    st[4 * i + 2 * h + 1] = (st[4 * i + 2 * h + 1] * kScale + (1.0f - mb) * -1.0e9f) * kLog2e;
                }
            }
            m0 = fmaxf(st[0], st[1]);
            m1 = fmaxf(st[2], st[3]);
#pragma unroll
            for (int i = 1; i < 4; i++) {
                m0 = fmaxf(m0, fmaxf(st[4 * i], st[4 * i + 1]));
                m1 = fmaxf(m1, fmaxf(st[4 * i + 2], st[4 * i + 3]));
            }
            m0 = quad_max(m0);
            m1 = quad_max(m1);
            l0 = 0.f;
            l1 = 0.f;
#pragma unroll
            for (int i = 0; i < 4; i++) {
                const float a = ex2(st[4 * i] - m0), b = ex2(st[4 * i + 1] - m0);
                const float e = ex2(st[4 * i + 2] - m1), f = ex2(st[4 * i + 3] - m1);
                l0 += a + b;
                l1 += e + f;
                p[2 * i] = pack_bf16(a, b);
                p[2 * i + 1] = pack_bf16(e, f);
            }
        }
        bool pending = true;
#pragma unroll 1
        for (int kt = 0;;) {
            const bool pv_only = pending && kt > 0 && !(kt & 1) && kt <= kPairEnd;
            const bool tree = kt == 0;
            const bool hand_over = wg == 0 || kt < kTiles - 1;
            if (!pv_only) {
                const uint64_t dk = db + (kOffRing >> 4) + r.s * (kTileBytes >> 4);
                mbar_wait(bar_full + 8 * (r.s * kSub), r.ph);
                wg_fence();
#pragma unroll
                for (int k = 0; k < 8; k++) {
                    const uint32_t off = ((k >> 2) * 1024 + (k & 3) * 32) >> 4;
                    wgmma_qk64<0>(sc, dq + off, dk + off, k != 0);
                }
                wg_commit();
                mbar_wait(bar_full + 8 * (r.s * kSub + 2), r.ph);
                bar_sync(1 + wg);
                wg_fence();
#pragma unroll
                for (int k = 0; k < 8; k++) {
                    const uint32_t off = ((k >> 2) * 1024 + (k & 3) * 32) >> 4;
                    wgmma_qk64<32>(sc, dq + off, dk + (16384 >> 4) + off, k != 0);
                }
                wg_commit();
                if (hand_over) bar_arrive(2 - wg);
                wg_wait<1>();
                fence_regs<0, 32>(sc);
                float x0 = fmaxf(sc[0], sc[1]), x1 = fmaxf(sc[2], sc[3]);
#pragma unroll
                for (int i = 1; i < 8; i++) {
                    x0 = fmaxf(x0, fmaxf(sc[4 * i], sc[4 * i + 1]));
                    x1 = fmaxf(x1, fmaxf(sc[4 * i + 2], sc[4 * i + 3]));
                }
                asm volatile("" : "+f"(x0), "+f"(x1)::"memory");
                wg_wait<0>();
                fence_regs<32, 64>(sc);
                if (lane == 0) mbar_arrive(bar_empty + 8 * r.s);
                r.next();

#pragma unroll
                for (int i = 8; i < 16; i++) {
                    x0 = fmaxf(x0, fmaxf(sc[4 * i], sc[4 * i + 1]));
                    x1 = fmaxf(x1, fmaxf(sc[4 * i + 2], sc[4 * i + 3]));
                }
                float n0 = fmaxf(m0, quad_max(x0) * c), n1 = fmaxf(m1, quad_max(x1) * c);
                moved = __any_sync(0xffffffffu, n0 > m0 || n1 > m1);
                {
                    float z;
                    asm volatile("st.volatile.shared.f32 [%2 + 4], %3;\n"
                                 "barrier.sync %1, 256;\nld.volatile.shared.f32 %0, [%2];"
                                 : "=f"(z) : "r"(3 + wg), "r"(pace_slot + 8), "f"(n0 + n1) : "memory");
                    n0 += z;
                    n1 += z;
                }
                a0 = ex2(m0 - n0);
                a1 = ex2(m1 - n1);
                m0 = n0;
                m1 = n1;
                l0 *= a0;
                l1 *= a1;
#pragma unroll
                for (int i = 0; i < 16; i++) {
                    sc[4 * i] = ex2(fmaf(sc[4 * i], c, -n0));
                    sc[4 * i + 1] = ex2(fmaf(sc[4 * i + 1], c, -n0));
                    sc[4 * i + 2] = ex2(fmaf(sc[4 * i + 2], c, -n1));
                    sc[4 * i + 3] = ex2(fmaf(sc[4 * i + 3], c, -n1));
                    l0 += sc[4 * i] + sc[4 * i + 1];
                    l1 += sc[4 * i + 2] + sc[4 * i + 3];
                }
                {
                    asm volatile("st.volatile.shared.f32 [%0], %1;" ::"r"(pace_slot + 12), "f"(sc[59]) : "memory");
                    if (hand_over) bar_arrive(4 - wg);
                }
                if (++kt == kTiles) break;
                if (kt == kTiles - 1) {
                    b0 = a0;
                    b1 = a1;
#pragma unroll
                    for (int i = 0; i < 16; i++) {
                        p[32 + 2 * i] = pack_bf16(sc[4 * i], sc[4 * i + 1]);
                        p[32 + 2 * i + 1] = pack_bf16(sc[4 * i + 2], sc[4 * i + 3]);
                    }
                    continue;
                }
            }

            if (pending) {
                const uint64_t dv = db + (kOffRing >> 4) + r.s * (kTileBytes >> 4);
                const uint32_t vbar = bar_full + 8 * (r.s * kSub);
                if (!tree) mbar_wait(vbar, r.ph);
                pv_piece(o, p, tree ? db + (kOffVt >> 4) : dv);
                if (!tree) {
#pragma unroll
                    for (int u = 1; u < 4; u++) {
                        mbar_wait(vbar + 8 * u, r.ph);
                        pv_piece(o, p + 8 * u, dv + u * (kSubBytes >> 4));
                    }
                }
            }
            wg_wait<0>();
            fence_regs<0, 64>(o);
            if (pending && !tree) {
                if (lane == 0) mbar_arrive(bar_empty + 8 * r.s);
                r.next();
            }
            pending = !pv_only;
            if (!pv_only) {
                if (moved) {
#pragma unroll
                    for (int i = 0; i < 16; i++) {
                        o[4 * i] *= a0;
                        o[4 * i + 1] *= a0;
                        o[4 * i + 2] *= a1;
                        o[4 * i + 3] *= a1;
                    }
                }
#pragma unroll
                for (int i = 0; i < 16; i++) {
                    p[2 * i] = pack_bf16(sc[4 * i], sc[4 * i + 1]);
                    p[2 * i + 1] = pack_bf16(sc[4 * i + 2], sc[4 * i + 3]);
                }
            }
        }

        float ol[32], oa[16], ob[16];
        {
            constexpr int it = kItems - 3;
            float i0, i1;
#pragma unroll
            for (int u = 0; u < 4; u++) {
                mbar_wait(bar_full + 8 * (it % kStages * kSub + u), it / kStages & 1);
                pv_piece(o, p + 8 * u, db + ((kOffRing + it % kStages * kTileBytes + u * kSubBytes) >> 4));
                if (u == 0) {
                    i0 = rcp(quad_sum(l0));
                    i1 = rcp(quad_sum(l1));
                    a0 *= i0;
                    a1 *= i1;
                }
#pragma unroll
                for (int i = 4 * u; i < 4 * u + 4; i++) {
                    uint32_t* q = p + 32 + 2 * i;
                    q[0] = pack_bf16(__uint_as_float(q[0] << 16) * a0, __uint_as_float(q[0] & 0xffff0000u) * a0);
                    q[1] = pack_bf16(__uint_as_float(q[1] << 16) * a1, __uint_as_float(q[1] & 0xffff0000u) * a1);
                    q[32] = pack_bf16(sc[4 * i] * i0, sc[4 * i + 1] * i0);
                    q[33] = pack_bf16(sc[4 * i + 2] * i1, sc[4 * i + 3] * i1);
                    asm volatile("" : "+r"(q[0]), "+r"(q[1]), "+r"(q[32]), "+r"(q[33])::"memory");
                }
            }
            b0 *= a0;
            b1 *= a1;
            wg_wait<0>();
            fence_regs<0, 64>(o);
#pragma unroll
            for (int i = 0; i < 64; i++) (i < 32 ? ol[i] : i < 48 ? oa[i - 32] : ob[i - 48]) = o[i] * ((i & 2) ? b1 : b0);
        }
        const uint32_t stg = sb + kOffQ + wg * 16384;
        const uint32_t st_h = stg + (warp & 3) * 2048 + (lane & 7) * 128 + (((lane >> 3) ^ (lane & 7)) << 4);
        const uint32_t st_q = stg + (warp & 3) * 1024 + (lane & 7) * 64 + (((lane >> 3) ^ ((lane >> 1) & 3)) << 4);
        auto stage = [&](uint32_t addr, const float* v) {
            asm volatile("stmatrix.sync.aligned.m8n8.x4.shared.b16 [%0], {%1, %2, %3, %4};"
                         ::"r"(addr), "r"(pack_bf16(v[0], v[1])), "r"(pack_bf16(v[4], v[5])), "r"(pack_bf16(v[8], v[9])),
                           "r"(pack_bf16(v[12], v[13])) : "memory");
        };
        uint4* gp = reinterpret_cast<uint4*>(out + (size_t)(cta * kRows + warp * 16 + (lane >> 2)) * kD + 96) + (lane & 3);
        uint32_t ld_q = stg + 12288 + (warp & 3) * 1024 + (lane >> 2) * 64 + (((lane & 3) ^ (lane >> 3)) << 4);
        asm volatile("" : "+l"(gp), "+r"(ld_q)::"memory");
        const uint64_t dh = make_desc(sb, 1024, 1), dq4 = make_desc(sb, 512, 2);
        static_for<0, kEndLoads>([&](auto jc) {
            constexpr int j = jc.value;
            constexpr EndLoad e = end_load(j);
            const uint64_t d = (e.cols == F ? db : e.cols <= R ? dh : dq4) + ((kOffEnd + end_pos(j)) >> 4);
            auto pv = [&](auto& acc, int off) {
#pragma unroll
                for (int k = 0; k < e.nk; k++) wgmma_pv(acc, p + 32 + 4 * (e.k0 + k), d + ((k * step_bytes(e.cols) + off) >> 4));
                wg_commit();
            };
            if (e.cols != A) {
                mbar_wait(bar_end + 8 * e.bar, 0);
                wg_fence();
            }
            if (e.cols == F || e.cols == L) pv(ol, 0);
            if (e.cols == F || e.cols == R || e.cols == A) pv(oa, e.cols == F ? 1024 : 0);
            if (e.cols == F || e.cols == R || e.cols == B) pv(ob, e.cols == F ? 1024 + 64 : e.cols == R ? 64 : 0);
            if (e.bar == kBarL) {
                wg_wait<2>();
                fence_regs<0, 32>(ol);
                stage(st_h, ol);
                stage(st_h ^ 64, ol + 16);
                stage(st_h + 1024, ol + 2);
                stage((st_h ^ 64) + 1024, ol + 18);
                asm volatile("barrier.arrive %0, 160;" ::"r"(5 + wg) : "memory");
            }
            if (e.bar == kBarA) {
                wg_wait<1>();
                fence_regs<0, 16>(oa);
                stage(st_q + 8192, oa);
                stage(st_q + 8192 + 512, oa + 2);
                asm volatile("barrier.arrive %0, 160;" ::"r"(8 + wg) : "memory");
            }
        });
        wg_wait<0>();
        fence_regs<0, 16>(ob);
        uint4 v[2];
#pragma unroll
        for (int j = 0; j < 2; j++) {
            stage(st_q + 12288 + 512 * j, ob + 2 * j);
            __syncwarp();
            asm volatile("ld.shared.v4.u32 {%0, %1, %2, %3}, [%4];" : "=r"(v[j].x), "=r"(v[j].y), "=r"(v[j].z), "=r"(v[j].w)
                         : "r"(ld_q + j * 512) : "memory");
        }
#pragma unroll
        for (int j = 0; j < 2; j++)
            asm volatile("st.global.v4.u32 [%0], {%1, %2, %3, %4};"
                         ::"l"(gp + 128 * j), "r"(v[j].x), "r"(v[j].y), "r"(v[j].z), "r"(v[j].w) : "memory");
    }
}

typedef CUresult (*EncodeFn)(CUtensorMap*, CUtensorMapDataType, cuuint32_t, void*, const cuuint64_t*,
                             const cuuint64_t*, const cuuint32_t*, const cuuint32_t*, CUtensorMapInterleave,
                             CUtensorMapSwizzle, CUtensorMapL2promotion, CUtensorMapFloatOOBfill);

void make_map(EncodeFn enc, CUtensorMap* m, const void* p, uint64_t rows, uint32_t box_rows, uint32_t box_cols) {
    const uint32_t w = box_cols == 32 ? 32 : 64;
    const cuuint64_t dims[4] = {w, 8, kD / w, rows / 8};
    const cuuint64_t strides[3] = {256, 2 * w, 2048};
    const cuuint32_t box[4] = {w, 8, box_cols / w, box_rows / 8};
    const cuuint32_t es[4] = {1, 1, 1, 1};
    enc(m, CU_TENSOR_MAP_DATA_TYPE_BFLOAT16, 4, const_cast<void*>(p), dims, strides, box, es,
        CU_TENSOR_MAP_INTERLEAVE_NONE, w == 64 ? CU_TENSOR_MAP_SWIZZLE_128B : CU_TENSOR_MAP_SWIZZLE_64B,
        box_cols == 128 ? CU_TENSOR_MAP_L2_PROMOTION_L2_256B
                        : box_cols == 64 ? CU_TENSOR_MAP_L2_PROMOTION_L2_128B : CU_TENSOR_MAP_L2_PROMOTION_NONE,
        CU_TENSOR_MAP_FLOAT_OOB_FILL_NONE);
}

}

extern "C" void kernel_launch(void* const* d_in, const int* in_sizes, int n_in, void* d_out, int out_size) {
    (void)in_sizes; (void)n_in; (void)out_size;
    static EncodeFn enc = nullptr;
    if (!enc) {
        cudaDriverEntryPointQueryResult qr;
        cudaGetDriverEntryPoint("cuTensorMapEncodeTiled", (void**)&enc, cudaEnableDefault, &qr);
        cudaFuncSetAttribute(tree_attn_kernel, cudaFuncAttributeMaxDynamicSharedMemorySize, kSmemBytes);
    }
    CUtensorMap tmQ, tmK, tmKt, tmVt, tmV, tmVh64, tmVh32, tmVq, tmOh, tmOq;
    make_map(enc, &tmQ, d_in[0], (uint64_t)kCtas * kRows, kRows, 128);
    make_map(enc, &tmK, d_in[1], (uint64_t)kCtas * kC, 32, 128);
    make_map(enc, &tmV, d_in[2], (uint64_t)kCtas * kC, 32, 128);
    make_map(enc, &tmVh64, d_in[2], (uint64_t)kCtas * kC, 64, 64);
    make_map(enc, &tmVh32, d_in[2], (uint64_t)kCtas * kC, 32, 64);
    make_map(enc, &tmVq, d_in[2], (uint64_t)kCtas * kC, 64, 32);
    make_map(enc, &tmKt, d_in[3], (uint64_t)kCtas * kT, kT, 128);
    make_map(enc, &tmVt, d_in[4], (uint64_t)kCtas * kT, kT, 128);
    make_map(enc, &tmOh, d_out, (uint64_t)kCtas * kRows, 64, 64);
    make_map(enc, &tmOq, d_out, (uint64_t)kCtas * kRows, 64, 32);
    tree_attn_kernel<<<kCtas, kThreads, kSmemBytes, cudaStreamPerThread>>>(
        (const __nv_bfloat16*)d_in[0], tmQ, tmK, tmKt, tmVt, tmV, tmVh64, tmVh32, tmVq, tmOh, tmOq,
        (const __nv_bfloat16*)d_in[5], (__nv_bfloat16*)d_out);
}
```

```cpp
#include <cuda_runtime.h>
#include <cuda_bf16.h>
#include <cuda.h>
#include <stdint.h>

namespace {

constexpr int kB = 16, kHq = 32, kHkv = 8, kT = 32, kC = 4096, kD = 128;
constexpr int kCtas = kB * kHkv;
constexpr int kRows = (kHq / kHkv) * kT;
constexpr int kTile = 128;
constexpr int kTiles = kC / kTile;
constexpr int kItems = 2 * kTiles;
constexpr int kTileBytes = kTile * kD * 2;
constexpr int kStages = 5;
constexpr int kSub = 4;
constexpr int kSubBytes = kTileBytes / kSub;
constexpr int kPairEnd = 28;
constexpr int kOddXor = 7;

constexpr int kUnit = 4800;
__host__ __device__ constexpr int clk(int units) { return units * kUnit / 256; }
constexpr int kWindow = 170;
constexpr int kWindowSlope = 2;
constexpr int kWindowExtra = 100;
constexpr int kStartT0 = 200;
constexpr uint32_t kPaceStart = 448;

constexpr int kOffQ = 0;
constexpr int kOffKt = 32768;
constexpr int kOffVt = kOffKt + 8192;
constexpr int kOffMask = kOffVt + 8192;
constexpr int kOffRing = kOffMask + 2048;
constexpr int kOffBar = kOffRing + kStages * kTileBytes;
constexpr int kSmemBytes = kOffBar + 512 + 1024;
constexpr int kThreads = 384;

__device__ unsigned int g_progress;

__device__ __forceinline__ uint32_t smem_u32(const void* p) { return (uint32_t)__cvta_generic_to_shared(p); }

__device__ __forceinline__ void mbar_init(uint32_t bar, uint32_t cnt) {
    asm volatile("mbarrier.init.shared::cta.b64 [%0], %1;" ::"r"(bar), "r"(cnt) : "memory");
}
__device__ __forceinline__ void mbar_expect_tx(uint32_t bar, uint32_t bytes) {
    asm volatile("mbarrier.arrive.expect_tx.shared::cta.b64 _, [%0], %1;" ::"r"(bar), "r"(bytes) : "memory");
}
__device__ __forceinline__ void mbar_arrive(uint32_t bar) {
    asm volatile("mbarrier.arrive.shared::cta.b64 _, [%0];" ::"r"(bar) : "memory");
}
__device__ __forceinline__ void mbar_wait(uint32_t bar, uint32_t parity) {
    asm volatile(
        "{\n.reg .pred p, q;\n.reg .u32 n;\nmov.u32 n, 0;\n"
        "WAIT_%=:\n"
        "mbarrier.try_wait.parity.shared::cta.b64 p, [%0], %1;\n"
        "add.u32 n, n, 1;\n"
        "setp.lt.and.u32 q, n, %2, !p;\n"
        "@q bra WAIT_%=;\n}"
        ::"r"(bar), "r"(parity), "n"(0x20000) : "memory");
}

__device__ __forceinline__ void tma_load(uint32_t dst, const CUtensorMap* m, uint32_t bar, int half, int grp) {
    asm volatile(
        "cp.async.bulk.tensor.4d.shared::cluster.global.mbarrier::complete_tx::bytes [%0], [%1, {%3, %3, %4, %5}], [%2];"
        ::"r"(dst), "l"(m), "r"(bar), "r"(0), "r"(half), "r"(grp) : "memory");
}
__device__ __forceinline__ void tma_stream(uint32_t dst, const CUtensorMap* m, uint32_t bar, int half, int grp, uint64_t pol) {
    asm volatile(
        "{\n.reg .pred p;\nelect.sync _|p, 0xffffffff;\n"
        "@p cp.async.bulk.tensor.4d.shared::cluster.global.mbarrier::complete_tx::bytes.L2::cache_hint"
        " [%0], [%1, {%3, %3, %4, %5}], [%2], %6;\n}"
        ::"r"(dst), "l"(m), "r"(bar), "r"(0), "r"(half), "r"(grp), "l"(pol) : "memory");
}
__device__ __forceinline__ void pace_wait(uint32_t slot, int due) {
    asm volatile(
        "{\n.reg .pred p;\n.reg .u32 t, c;\n"
        "PACE_%=:\n"
        "ld.volatile.shared.u32 t, [%0];\n"
        "mov.u32 c, %clock;\n"
        "sub.u32 c, c, t;\n"
        "setp.lt.s32 p, c, %1;\n"
        "@p bra.uni PACE_%=;\n}"
        ::"r"(slot), "r"(due) : "memory");
}
__device__ __forceinline__ void prefetch_map(const CUtensorMap* m) {
    asm volatile("prefetch.tensormap [%0];" ::"l"(m) : "memory");
}

__device__ __forceinline__ uint64_t make_desc(uint32_t addr, uint32_t sbo, uint64_t swizzle) {
    return (uint64_t)((addr & 0x3FFFF) >> 4) | (1ull << 16) | ((uint64_t)(sbo >> 4) << 32) | (swizzle << 62);
}

__device__ __forceinline__ void wg_fence() { asm volatile("wgmma.fence.sync.aligned;" ::: "memory"); }
__device__ __forceinline__ void wg_commit() { asm volatile("wgmma.commit_group.sync.aligned;" ::: "memory"); }
template <int N> __device__ __forceinline__ void wg_wait() { asm volatile("wgmma.wait_group.sync.aligned %0;" ::"n"(N) : "memory"); }
template <int LO, int HI, int N> __device__ __forceinline__ void fence_regs(float (&r)[N]) {
#pragma unroll
    for (int i = LO; i < HI; i++) asm volatile("" : "+f"(r[i])::"memory");
}
__device__ __forceinline__ void bar_sync(int id) { asm volatile("barrier.sync %0, 256;" ::"r"(id) : "memory"); }
__device__ __forceinline__ void bar_arrive(int id) { asm volatile("barrier.arrive %0, 256;" ::"r"(id) : "memory"); }

#define ACC8(d, o) "+f"(d[o]), "+f"(d[o + 1]), "+f"(d[o + 2]), "+f"(d[o + 3]), "+f"(d[o + 4]), "+f"(d[o + 5]), "+f"(d[o + 6]), "+f"(d[o + 7])
#define ACC32(d, o) ACC8(d, o), ACC8(d, o + 8), ACC8(d, o + 16), ACC8(d, o + 24)
#define REGS16 "%0, %1, %2, %3, %4, %5, %6, %7, %8, %9, %10, %11, %12, %13, %14, %15"
#define REGS32 "%16, %17, %18, %19, %20, %21, %22, %23, %24, %25, %26, %27, %28, %29, %30, %31"
#define REGS64                                                                          \
    "%32, %33, %34, %35, %36, %37, %38, %39, %40, %41, %42, %43, %44, %45, %46, %47, " \
    "%48, %49, %50, %51, %52, %53, %54, %55, %56, %57, %58, %59, %60, %61, %62, %63"

template <int O>
__device__ __forceinline__ void wgmma_qk64(float (&d)[64], uint64_t da, uint64_t db, int acc) {
    asm volatile(
        "{\n.reg .pred p;\nsetp.ne.b32 p, %34, 0;\n"
        "wgmma.mma_async.sync.aligned.m64n64k16.f32.bf16.bf16 {" REGS16 ", " REGS32 "}, %32, %33, p, 1, 1, 0, 0;\n}"
        : ACC32(d, O) : "l"(da), "l"(db), "r"(acc));
}
__device__ __forceinline__ void wgmma_qk32(float (&d)[16], uint64_t da, uint64_t db, int acc) {
    asm volatile(
        "{\n.reg .pred p;\nsetp.ne.b32 p, %18, 0;\n"
        "wgmma.mma_async.sync.aligned.m64n32k16.f32.bf16.bf16 {" REGS16 "}, %16, %17, p, 1, 1, 0, 0;\n}"
        : ACC8(d, 0), ACC8(d, 8) : "l"(da), "l"(db), "r"(acc));
}
__device__ __forceinline__ void wgmma_pv(float (&d)[64], const uint32_t* a, uint64_t db) {
    asm volatile(
        "{\n.reg .pred p;\nsetp.ne.b32 p, 1, 0;\n"
        "wgmma.mma_async.sync.aligned.m64n128k16.f32.bf16.bf16 {" REGS16 ", " REGS32 ", " REGS64 "}, {%64, %65, %66, %67}, %68, p, 1, 1, 1;\n}"
        : ACC32(d, 0), ACC32(d, 32) : "r"(a[0]), "r"(a[1]), "r"(a[2]), "r"(a[3]), "l"(db));
}
__device__ __forceinline__ void wgmma_pv(float (&d)[32], const uint32_t* a, uint64_t db) {
    asm volatile(
        "{\n.reg .pred p;\nsetp.ne.b32 p, 1, 0;\n"
        "wgmma.mma_async.sync.aligned.m64n64k16.f32.bf16.bf16 {" REGS16 ", " REGS32 "}, {%32, %33, %34, %35}, %36, p, 1, 1, 1;\n}"
        : ACC32(d, 0) : "r"(a[0]), "r"(a[1]), "r"(a[2]), "r"(a[3]), "l"(db));
}
__device__ __forceinline__ void wgmma_pv(float (&d)[16], const uint32_t* a, uint64_t db) {
    asm volatile(
        "{\n.reg .pred p;\nsetp.ne.b32 p, 1, 0;\n"
        "wgmma.mma_async.sync.aligned.m64n32k16.f32.bf16.bf16 {" REGS16 "}, {%16, %17, %18, %19}, %20, p, 1, 1, 1;\n}"
        : ACC8(d, 0), ACC8(d, 8) : "r"(a[0]), "r"(a[1]), "r"(a[2]), "r"(a[3]), "l"(db));
}
__device__ __forceinline__ void pv_piece(float (&o)[64], const uint32_t* a, uint64_t dv) {
    dv += ((1024 >> 4) - 1) << 16;
    wg_fence();
    wgmma_pv(o, a, dv);
    wgmma_pv(o, a + 4, dv + (4096 >> 4));
    wg_commit();
}

__device__ __forceinline__ float ex2(float x) {
    float y;
    asm("ex2.approx.ftz.f32 %0, %1;" : "=f"(y) : "f"(x));
    return y;
}
__device__ __forceinline__ float rcp(float x) {
    float y;
    asm("rcp.approx.ftz.f32 %0, %1;" : "=f"(y) : "f"(x));
    return y;
}
__device__ __forceinline__ uint32_t pack_bf16(float lo, float hi) {
    uint32_t r;
    asm("cvt.rn.bf16x2.f32 %0, %1, %2;" : "=r"(r) : "f"(hi), "f"(lo));
    return r;
}
__device__ __forceinline__ uint32_t scale_bf16(uint32_t x, uint32_t hi, uint32_t lo) {
    uint32_t r;
    asm("{\n.reg .b32 t;\nmul.rn.bf16x2 t, %1, %3;\nfma.rn.bf16x2 %0, %1, %2, t;\n}" : "=r"(r) : "r"(x), "r"(hi), "r"(lo));
    return r;
}
__device__ __forceinline__ float quad_max(float x) {
    x = fmaxf(x, __shfl_xor_sync(0xffffffffu, x, 1));
    return fmaxf(x, __shfl_xor_sync(0xffffffffu, x, 2));
}
__device__ __forceinline__ float quad_sum(float x) {
    x += __shfl_xor_sync(0xffffffffu, x, 1);
    return x + __shfl_xor_sync(0xffffffffu, x, 2);
}

template <int V> struct IntC { static constexpr int value = V; };
template <int I, int N, class Fn> __device__ __forceinline__ void static_for(Fn&& f) {
    if constexpr (I < N) {
        f(IntC<I>{});
        static_for<I + 1, N>(f);
    }
}
struct Ring {
    int s;
    uint32_t ph;
    __device__ __forceinline__ void next() { if (++s == kStages) { s = 0; ph ^= 1; } }
};

__device__ __forceinline__ bool item_is_v(int i) {
    return i < 2 * kPairEnd ? (i & 2) != 0 : i >= kItems - 4 ? i != kItems - 4 : (i > 2 * kPairEnd && !(i & 1));
}
__device__ __forceinline__ int item_tile(int i) {
    return i < 2 * kPairEnd ? (i >> 2) * 2 + (i & 1) : i == kItems - 4 ? kTiles - 1 : item_is_v(i) ? (i >> 1) - 1 : (i + 1) >> 1;
}

enum { F, L, R, A, B };
struct EndLoad { int cols, blk, bar; };
constexpr int kEndLoads = 15, kEndBars = 13;
__host__ __device__ constexpr EndLoad end_load(int j) {
    constexpr EndLoad t[kEndLoads] = {{L, 0, 0}, {L, 1, 1}, {L, 2, 2}, {A, 2, 2}, {L, 3, 3},  {A, 3, 3},  {L, 4, 4}, {F, 5, 5},
                                      {F, 6, 6}, {F, 7, 7}, {R, 4, 8}, {R, 0, 9}, {R, 1, 10}, {B, 2, 11}, {B, 3, 12}};
    return t[j];
}
constexpr int kBarHalf = 5, kBarL = 7, kBarA = 10;
__host__ __device__ constexpr int load_bytes(int cols) { return cols == F ? 8192 : cols <= R ? 4096 : 2048; }
__host__ __device__ constexpr int end_pos(int j) { return j ? end_pos(j - 1) + load_bytes(end_load(j - 1).cols) : 0; }
__host__ __device__ constexpr int bar_bytes(int x) {
    int n = 0;
    for (int j = 0; j < kEndLoads; j++) n += end_load(j).bar == x ? end_pos(j + 1) - end_pos(j) : 0;
    return n;
}
constexpr int kOffEnd = kOffRing + (kItems - 2) % kStages * kTileBytes;
static_assert((kItems - 2) % kStages + 1 < kStages && end_pos(kEndLoads) == 2 * kTileBytes, "two adjacent slots");

__global__ void __launch_bounds__(kThreads, 1)
tree_attn_kernel(const __nv_bfloat16* __restrict__ q,
                 const __grid_constant__ CUtensorMap tmQ, const __grid_constant__ CUtensorMap tmK,
                 const __grid_constant__ CUtensorMap tmKt, const __grid_constant__ CUtensorMap tmVt,
                 const __grid_constant__ CUtensorMap tmV, const __grid_constant__ CUtensorMap tmVh,
                 const __grid_constant__ CUtensorMap tmVq, const __grid_constant__ CUtensorMap tmOh,
                 const __grid_constant__ CUtensorMap tmOq,
                 const __nv_bfloat16* __restrict__ mask, __nv_bfloat16* __restrict__ out) {
    extern __shared__ uint8_t smem_raw[];
    if (threadIdx.x == 0)
        asm volatile("cp.async.bulk.prefetch.L2.global [%0], 32768;" ::"l"(q + (size_t)blockIdx.x * kRows * kD));
    const uint32_t sb = (smem_u32(smem_raw) + 1023u) & ~1023u;
    const uint32_t bar_q = sb + kOffBar;
    const uint32_t bar_empty = bar_q + 8;
    const uint32_t bar_full = bar_empty + 8 * kStages;
    const uint32_t bar_end = bar_full + 8 * kStages * kSub;
    const uint32_t pace_slot = sb + kOffBar + 448;
    const uint32_t done_flag = pace_slot + 4;
    static_assert(8 * (1 + kStages + kStages * kSub + kEndBars) <= 448, "barrier area");
    const int cta = blockIdx.x;

    if (threadIdx.x == 256) {
        mbar_init(bar_q, 1);
        asm volatile("fence.mbarrier_init.release.cluster;" ::: "memory");
        mbar_expect_tx(bar_q, 32768 + 16384 + 2048);
        tma_load(sb + kOffQ, &tmQ, bar_q, 0, cta * (kRows / 8));
        tma_load(sb + kOffKt, &tmKt, bar_q, 0, cta * (kT / 8));
        tma_load(sb + kOffVt, &tmVt, bar_q, 0, cta * (kT / 8));
        asm volatile("cp.async.bulk.shared::cluster.global.mbarrier::complete_tx::bytes [%0], [%1], 2048, [%2];"
                     ::"r"(sb + kOffMask), "l"(mask + (cta / kHkv) * kT * kT), "r"(bar_q) : "memory");
#pragma unroll
        for (int i = 0; i < kStages; i++) mbar_init(bar_empty + 8 * i, 9);
#pragma unroll
        for (int i = 0; i < kStages * kSub + kEndBars; i++) mbar_init(bar_full + 8 * i, 1);
        asm volatile("st.shared.v4.u32 [%0], {%1, %2, %2, %2};"
                     ::"r"(pace_slot), "r"((uint32_t)clock() + (kStartT0 + clk(kWindow + kWindowExtra))), "r"(0) : "memory");
        asm volatile("fence.mbarrier_init.release.cluster;" ::: "memory");
    }
    __syncwarp();
    const int warp = __shfl_sync(0xffffffffu, threadIdx.x >> 5, 0);
    const int lane = threadIdx.x & 31;

    if (warp >= 8) {
        asm volatile("setmaxnreg.dec.sync.aligned.u32 40;");
        if (warp == 8) {
            asm volatile("barrier.arrive 7, 352;" ::: "memory");
            uint64_t pol;
            asm volatile("createpolicy.fractional.L2::evict_first.b64 %0, 1.0;" : "=l"(pol));
            if (lane == 0) static_for<0, kEndBars>([&](auto x) { mbar_expect_tx(bar_end + 8 * x.value, bar_bytes(x.value)); });
            __syncwarp();
            Ring r{0, 1};
            const int g0 = cta * (kC / 8), gx = (cta & 1) * kOddXor * 8;
            int due = -clk(kWindow), extra = (kItems * kSub - 1) * clk(kWindowSlope);
#pragma unroll 1
            for (int i = 0; i < kItems - 2; i++) {
                const bool isv = item_is_v(i);
                const CUtensorMap* tm = isv ? &tmV : &tmK;
                const uint32_t bar = bar_full + 8 * (r.s * kSub), dst = sb + kOffRing + r.s * kTileBytes;
                const int grp = item_tile(i) * (kTile / 8);
                mbar_wait(bar_empty + 8 * r.s, r.ph);
                if (lane < kSub) mbar_expect_tx(bar + 8 * lane, isv ? kSubBytes : (lane & 1) ? 0 : 2 * kSubBytes);
                __syncwarp();
#pragma unroll
                for (int u = 0; u < kSub; u++) {
                    pace_wait(pace_slot, due - min(clk(kWindowExtra), extra));
                    tma_stream(dst + u * kSubBytes, tm, bar + 8 * (isv ? u : u & 2), 0, g0 + ((grp + 4 * u) ^ gx), pol);
                    due += clk(kCtas / kSub);
                    extra -= clk(kWindowSlope);
                }
                r.next();
            }
            static_for<0, kEndLoads>([&](auto jc) {
                constexpr int j = jc.value;
                constexpr EndLoad e = end_load(j);
                if (end_pos(j) % kTileBytes == 0) {
                    mbar_wait(bar_empty + 8 * r.s, r.ph);
                    __syncwarp();
                    r.next();
                }
                if (e.cols != A) {
                    constexpr int mid = end_pos(j) + bar_bytes(e.bar) / 2;
                    constexpr int pos = mid + (e.bar > kBarL ? (mid - 6 * kSubBytes) / 4 : 0) - kSubBytes / 2;
                    pace_wait(pace_slot, due + clk(pos / 256) - (7 * kSubBytes - pos) / 1024 * clk(kWindowSlope) / 8);
                }
                tma_stream(sb + kOffEnd + end_pos(j), e.cols == F ? &tmV : e.cols <= R ? &tmVh : &tmVq, bar_end + 8 * e.bar,
                           e.cols == F ? 0 : e.cols - 1, g0 + (((kTiles - 2) * (kTile / 8) + 4 * e.blk) ^ gx), pol);
            });
            asm volatile("barrier.arrive 10, 96;" ::: "memory");
            if (lane == 0) asm volatile("st.volatile.shared.u32 [%0], %1;" ::"r"(done_flag), "r"(1) : "memory");
        } else if (warp == 9) {
            if (lane == 0) {
                prefetch_map(&tmK);
                prefetch_map(&tmV);
                prefetch_map(&tmVh);
                prefetch_map(&tmVq);
                prefetch_map(&tmOh);
                prefetch_map(&tmOq);
            }
            __syncwarp();
            asm volatile("barrier.sync 7, 352;" ::: "memory");
            if (lane == 0) {
                uint32_t org = 0, g_seen = 0, t_seen = clock();
                while (true) {
                    uint32_t g, done;
                    const uint32_t t = clock();
                    asm volatile("ld.relaxed.gpu.global.u32 %0, [%1];" : "=r"(g) : "l"(&g_progress) : "memory");
                    if (g < g_seen) break;
                    if (g > g_seen) t_seen = t;
                    const uint32_t x = t - ((g * kUnit) >> 8);
                    org = g_seen < 3 * kCtas ? x : org + ((int)(x - org) >> 2);
                    g_seen = g;
                    if (t - t_seen > 60000u) {
                        asm volatile("st.volatile.shared.u32 [%0], %1;" ::"r"(pace_slot), "r"(t - 0x400000u) : "memory");
                        break;
                    }
                    if (g >= kPaceStart) asm volatile("st.volatile.shared.u32 [%0], %1;" ::"r"(pace_slot), "r"(org) : "memory");
                    asm volatile("ld.volatile.shared.u32 %0, [%1];" : "=r"(done) : "r"(done_flag) : "memory");
                    if (done) break;
                }
            }
        } else {
            if (warp == 10) {
                asm volatile("barrier.sync 7, 352;" ::: "memory");
                Ring r{0, 0};
#pragma unroll 1
                for (int i = 0; i < kItems - 1; i++) {
                    const bool isv = item_is_v(i);
                    if (i == kItems - 2) mbar_wait(bar_end + 8 * kBarHalf, 0);
                    else mbar_wait(bar_full + 8 * (r.s * kSub + (isv ? 3 : 2)), r.ph);
                    asm volatile("{\n.reg .pred p;\nsetp.eq.u32 p, %2, 0;\n@p red.relaxed.gpu.global.inc.u32 [%0], %1;\n}"
                                 ::"l"(&g_progress), "n"(kCtas * (kItems - 1) - 1), "r"(lane) : "memory");
                    if (!isv) {
                        mbar_wait(bar_full + 8 * (r.s * kSub + 1), r.ph);
                        mbar_wait(bar_full + 8 * (r.s * kSub + 3), r.ph);
                    }
                    __syncwarp();
                    asm volatile("{\n.reg .pred p;\nsetp.eq.u32 p, %1, 0;\n@p mbarrier.arrive.shared::cta.b64 _, [%0];\n}"
                                 ::"r"(bar_empty + 8 * r.s), "r"(lane) : "memory");
                    r.next();
                }
            }
            const int g = 11 - warp;
            asm volatile("barrier.sync 10, 96;" ::: "memory");
#pragma unroll
            for (int i = 0; i < 2; i++)
                asm volatile("barrier.sync %0, 160;\nfence.proxy.async.shared::cta;\n"
                             "{\n.reg .pred p;\nelect.sync _|p, 0xffffffff;\n"
                             "@p cp.async.bulk.tensor.4d.global.shared::cta.bulk_group [%1, {%3, %3, %4, %5}], [%2];\n}"
                             ::"r"(5 + 3 * i + g), "l"(i ? &tmOq : &tmOh), "r"(sb + kOffQ + g * 16384 + i * 8192), "r"(0), "r"(2 * i),
                               "r"(cta * (kRows / 8) + g * 8) : "memory");
            asm volatile("cp.async.bulk.commit_group;\ncp.async.bulk.wait_group.read 0;" ::: "memory");
        }
    } else {
        asm volatile("setmaxnreg.inc.sync.aligned.u32 232;");
        const int wg = warp >> 2;
        const float kScale = 0.08838834764831845f;
        const float kLog2e = 1.4426950408889634f;
        const float c = kScale * kLog2e;
        if (wg == 1) {
            bar_arrive(1);
            bar_arrive(3);
        }

        const uint64_t db = make_desc(sb, 2048, 1);
        const uint64_t dq = db + ((kOffQ + wg * 16384) >> 4);
        float o[64], sc[64];
        uint32_t p[96];
        float l0, l1, a0 = 1.f, a1 = 1.f, b0 = 1.f, b1 = 1.f;
        bool moved = false;
        Ring r{0, 0};
        float m0, m1;
#pragma unroll
        for (int i = 0; i < 64; i++) o[i] = sc[i] = 0.f, p[i] = 0;
        asm volatile("barrier.sync 7, 352;" ::: "memory");
        mbar_wait(bar_q, 0);
        {
            float st[16];
            const uint64_t dk = db + (kOffKt >> 4);
            wg_fence();
#pragma unroll
            for (int k = 0; k < 8; k++) {
                const uint32_t off = ((k >> 2) * 1024 + (k & 3) * 32) >> 4;
                wgmma_qk32(st, dq + off, dk + off, k != 0);
            }
            wg_commit();
            wg_wait<0>();
            fence_regs<0, 16>(st);
#pragma unroll
            for (int i = 0; i < 4; i++) {
#pragma unroll
                for (int h = 0; h < 2; h++) {
                    uint32_t w;
                    asm volatile("ld.shared.u32 %0, [%1];" : "=r"(w)
                                 : "r"(sb + kOffMask + ((warp & 1) * 16 + (lane >> 2) + 8 * h) * 64 + 16 * i + 4 * (lane & 3)));
                    const float ma = __uint_as_float(w << 16), mb = __uint_as_float(w & 0xffff0000u);
                    st[4 * i + 2 * h] = (st[4 * i + 2 * h] * kScale + (1.0f - ma) * -1.0e9f) * kLog2e;
                    st[4 * i + 2 * h + 1] = (st[4 * i + 2 * h + 1] * kScale + (1.0f - mb) * -1.0e9f) * kLog2e;
                }
            }
            m0 = fmaxf(st[0], st[1]);
            m1 = fmaxf(st[2], st[3]);
#pragma unroll
            for (int i = 1; i < 4; i++) {
                m0 = fmaxf(m0, fmaxf(st[4 * i], st[4 * i + 1]));
                m1 = fmaxf(m1, fmaxf(st[4 * i + 2], st[4 * i + 3]));
            }
            m0 = quad_max(m0);
            m1 = quad_max(m1);
            l0 = 0.f;
            l1 = 0.f;
#pragma unroll
            for (int i = 0; i < 4; i++) {
                const float a = ex2(st[4 * i] - m0), b = ex2(st[4 * i + 1] - m0);
                const float e = ex2(st[4 * i + 2] - m1), f = ex2(st[4 * i + 3] - m1);
                l0 += a + b;
                l1 += e + f;
                p[2 * i] = pack_bf16(a, b);
                p[2 * i + 1] = pack_bf16(e, f);
            }
        }
        bool pending = true;
#pragma unroll 1
        for (int kt = 0;;) {
            const bool pv_only = pending && kt > 0 && !(kt & 1) && kt <= kPairEnd;
            const bool tree = kt == 0;
            const bool hand_over = wg == 0 || kt < kTiles - 1;
            if (!pv_only) {
                const uint64_t dk = db + (kOffRing >> 4) + r.s * (kTileBytes >> 4);
                mbar_wait(bar_full + 8 * (r.s * kSub), r.ph);
                wg_fence();
#pragma unroll
                for (int k = 0; k < 8; k++) {
                    const uint32_t off = ((k >> 2) * 1024 + (k & 3) * 32) >> 4;
                    wgmma_qk64<0>(sc, dq + off, dk + off, k != 0);
                }
                wg_commit();
                mbar_wait(bar_full + 8 * (r.s * kSub + 2), r.ph);
                bar_sync(1 + wg);
                wg_fence();
#pragma unroll
                for (int k = 0; k < 8; k++) {
                    const uint32_t off = ((k >> 2) * 1024 + (k & 3) * 32) >> 4;
                    wgmma_qk64<32>(sc, dq + off, dk + (16384 >> 4) + off, k != 0);
                }
                wg_commit();
                if (hand_over) bar_arrive(2 - wg);
                wg_wait<1>();
                fence_regs<0, 32>(sc);
                float x0 = fmaxf(sc[0], sc[1]), x1 = fmaxf(sc[2], sc[3]);
#pragma unroll
                for (int i = 1; i < 8; i++) {
                    x0 = fmaxf(x0, fmaxf(sc[4 * i], sc[4 * i + 1]));
                    x1 = fmaxf(x1, fmaxf(sc[4 * i + 2], sc[4 * i + 3]));
                }
                asm volatile("" : "+f"(x0), "+f"(x1)::"memory");
                wg_wait<0>();
                fence_regs<32, 64>(sc);
                if (lane == 0) mbar_arrive(bar_empty + 8 * r.s);
                r.next();

#pragma unroll
                for (int i = 8; i < 16; i++) {
                    x0 = fmaxf(x0, fmaxf(sc[4 * i], sc[4 * i + 1]));
                    x1 = fmaxf(x1, fmaxf(sc[4 * i + 2], sc[4 * i + 3]));
                }
                float n0 = fmaxf(m0, quad_max(x0) * c), n1 = fmaxf(m1, quad_max(x1) * c);
                moved = __any_sync(0xffffffffu, n0 > m0 || n1 > m1);
                {
                    float z;
                    asm volatile("st.volatile.shared.f32 [%2 + 4], %3;\n"
                                 "barrier.sync %1, 256;\nld.volatile.shared.f32 %0, [%2];"
                                 : "=f"(z) : "r"(3 + wg), "r"(pace_slot + 8), "f"(n0 + n1) : "memory");
                    n0 += z;
                    n1 += z;
                }
                a0 = ex2(m0 - n0);
                a1 = ex2(m1 - n1);
                m0 = n0;
                m1 = n1;
                l0 *= a0;
                l1 *= a1;
#pragma unroll
                for (int i = 0; i < 16; i++) {
                    sc[4 * i] = ex2(fmaf(sc[4 * i], c, -n0));
                    sc[4 * i + 1] = ex2(fmaf(sc[4 * i + 1], c, -n0));
                    sc[4 * i + 2] = ex2(fmaf(sc[4 * i + 2], c, -n1));
                    sc[4 * i + 3] = ex2(fmaf(sc[4 * i + 3], c, -n1));
                    l0 += sc[4 * i] + sc[4 * i + 1];
                    l1 += sc[4 * i + 2] + sc[4 * i + 3];
                }
                {
                    asm volatile("st.volatile.shared.f32 [%0], %1;" ::"r"(pace_slot + 12), "f"(sc[59]) : "memory");
                    if (hand_over) bar_arrive(4 - wg);
                }
                if (++kt == kTiles) break;
                if (kt == kTiles - 1) {
                    b0 = a0;
                    b1 = a1;
#pragma unroll
                    for (int i = 0; i < 16; i++) {
                        p[32 + 2 * i] = pack_bf16(sc[4 * i], sc[4 * i + 1]);
                        p[32 + 2 * i + 1] = pack_bf16(sc[4 * i + 2], sc[4 * i + 3]);
                    }
                    continue;
                }
            }

            if (pending) {
                const uint64_t dv = db + (kOffRing >> 4) + r.s * (kTileBytes >> 4);
                const uint32_t vbar = bar_full + 8 * (r.s * kSub);
                if (!tree) mbar_wait(vbar, r.ph);
                pv_piece(o, p, tree ? db + (kOffVt >> 4) : dv);
                if (!tree) {
#pragma unroll
                    for (int u = 1; u < 4; u++) {
                        mbar_wait(vbar + 8 * u, r.ph);
                        pv_piece(o, p + 8 * u, dv + u * (kSubBytes >> 4));
                    }
                }
            }
            wg_wait<0>();
            fence_regs<0, 64>(o);
            if (pending && !tree) {
                if (lane == 0) mbar_arrive(bar_empty + 8 * r.s);
                r.next();
            }
            pending = !pv_only;
            if (!pv_only) {
                if (moved) {
#pragma unroll
                    for (int i = 0; i < 16; i++) {
                        o[4 * i] *= a0;
                        o[4 * i + 1] *= a0;
                        o[4 * i + 2] *= a1;
                        o[4 * i + 3] *= a1;
                    }
                }
#pragma unroll
                for (int i = 0; i < 16; i++) {
                    p[2 * i] = pack_bf16(sc[4 * i], sc[4 * i + 1]);
                    p[2 * i + 1] = pack_bf16(sc[4 * i + 2], sc[4 * i + 3]);
                }
            }
        }

        float ol[32], oa[16], ob[16];
        {
            constexpr int it = kItems - 3;
            float i0, i1;
            uint32_t h0, h1, e0, e1;
#pragma unroll
            for (int u = 0; u < 4; u++) {
                mbar_wait(bar_full + 8 * (it % kStages * kSub + u), it / kStages & 1);
                pv_piece(o, p + 8 * u, db + ((kOffRing + it % kStages * kTileBytes + u * kSubBytes) >> 4));
                if (u == 0) {
                    i0 = rcp(quad_sum(l0));
                    i1 = rcp(quad_sum(l1));
                    a0 *= i0;
                    a1 *= i1;
                    h0 = pack_bf16(a0, a0);
                    h1 = pack_bf16(a1, a1);
                    const float r0 = a0 - __uint_as_float(h0 << 16), r1 = a1 - __uint_as_float(h1 << 16);
                    e0 = pack_bf16(r0, r0);
                    e1 = pack_bf16(r1, r1);
                }
#pragma unroll
                for (int i = 4 * u; i < 4 * u + 4; i++) {
                    uint32_t* q = p + 32 + 2 * i;
                    q[0] = scale_bf16(q[0], h0, e0);
                    q[1] = scale_bf16(q[1], h1, e1);
                    q[32] = pack_bf16(sc[4 * i] * i0, sc[4 * i + 1] * i0);
                    q[33] = pack_bf16(sc[4 * i + 2] * i1, sc[4 * i + 3] * i1);
                    asm volatile("" : "+r"(q[0]), "+r"(q[1]), "+r"(q[32]), "+r"(q[33])::"memory");
                }
            }
            b0 *= a0;
            b1 *= a1;
            wg_wait<0>();
            fence_regs<0, 64>(o);
#pragma unroll
            for (int i = 0; i < 64; i++) (i < 32 ? ol[i] : i < 48 ? oa[i - 32] : ob[i - 48]) = o[i] * ((i & 2) ? b1 : b0);
        }
        const uint32_t stg = sb + kOffQ + wg * 16384;
        const uint32_t st_h = stg + (warp & 3) * 2048 + (lane & 7) * 128 + (((lane >> 3) ^ (lane & 7)) << 4);
        const uint32_t st_q = stg + (warp & 3) * 1024 + (lane & 7) * 64 + (((lane >> 3) ^ ((lane >> 1) & 3)) << 4);
        auto stage = [&](uint32_t addr, const float* v) {
            asm volatile("stmatrix.sync.aligned.m8n8.x4.shared.b16 [%0], {%1, %2, %3, %4};"
                         ::"r"(addr), "r"(pack_bf16(v[0], v[1])), "r"(pack_bf16(v[4], v[5])), "r"(pack_bf16(v[8], v[9])),
                           "r"(pack_bf16(v[12], v[13])) : "memory");
        };
        uint4* gp = reinterpret_cast<uint4*>(out + (size_t)(cta * kRows + warp * 16 + (lane >> 2)) * kD + 96) + (lane & 3);
        uint32_t ld_q = stg + 12288 + (warp & 3) * 1024 + (lane >> 2) * 64 + (((lane & 3) ^ (lane >> 3)) << 4);
        asm volatile("" : "+l"(gp), "+r"(ld_q)::"memory");
        const uint64_t dh = make_desc(sb, 1024, 1), dq4 = make_desc(sb, 512, 2);
        static_for<0, kEndLoads>([&](auto jc) {
            constexpr int j = jc.value;
            constexpr EndLoad e = end_load(j);
            const uint64_t d = (e.cols == F ? db : e.cols <= R ? dh : dq4) + ((kOffEnd + end_pos(j)) >> 4);
            auto pv = [&](auto& acc, int off) {
                wgmma_pv(acc, p + 32 + 8 * e.blk, d + (off >> 4));
                wgmma_pv(acc, p + 36 + 8 * e.blk, d + ((off + load_bytes(e.cols) / 2) >> 4));
                wg_commit();
            };
            if (e.cols != A) {
                mbar_wait(bar_end + 8 * e.bar, 0);
                wg_fence();
            }
            if (e.cols == F || e.cols == L) pv(ol, 0);
            if (e.cols == F || e.cols == R || e.cols == A) pv(oa, e.cols == F ? 1024 : 0);
            if (e.cols == F || e.cols == R || e.cols == B) pv(ob, e.cols == F ? 1024 + 64 : e.cols == R ? 64 : 0);
            if (e.bar == kBarL) {
                wg_wait<2>();
                fence_regs<0, 32>(ol);
                stage(st_h, ol);
                stage(st_h ^ 64, ol + 16);
                stage(st_h + 1024, ol + 2);
                stage((st_h ^ 64) + 1024, ol + 18);
                asm volatile("barrier.arrive %0, 160;" ::"r"(5 + wg) : "memory");
            }
            if (e.bar == kBarA) {
                wg_wait<1>();
                fence_regs<0, 16>(oa);
                stage(st_q + 8192, oa);
                stage(st_q + 8192 + 512, oa + 2);
                asm volatile("barrier.arrive %0, 160;" ::"r"(8 + wg) : "memory");
            }
        });
        wg_wait<0>();
        fence_regs<0, 16>(ob);
        uint4 v[2];
#pragma unroll
        for (int j = 0; j < 2; j++) {
            stage(st_q + 12288 + 512 * j, ob + 2 * j);
            __syncwarp();
            asm volatile("ld.shared.v4.u32 {%0, %1, %2, %3}, [%4];" : "=r"(v[j].x), "=r"(v[j].y), "=r"(v[j].z), "=r"(v[j].w)
                         : "r"(ld_q + j * 512) : "memory");
        }
#pragma unroll
        for (int j = 0; j < 2; j++)
            asm volatile("st.global.v4.u32 [%0], {%1, %2, %3, %4};"
                         ::"l"(gp + 128 * j), "r"(v[j].x), "r"(v[j].y), "r"(v[j].z), "r"(v[j].w) : "memory");
    }
}

typedef CUresult (*EncodeFn)(CUtensorMap*, CUtensorMapDataType, cuuint32_t, void*, const cuuint64_t*,
                             const cuuint64_t*, const cuuint32_t*, const cuuint32_t*, CUtensorMapInterleave,
                             CUtensorMapSwizzle, CUtensorMapL2promotion, CUtensorMapFloatOOBfill);

void make_map(EncodeFn enc, CUtensorMap* m, const void* p, uint64_t rows, uint32_t box_rows, uint32_t box_cols) {
    const uint32_t w = box_cols == 32 ? 32 : 64;
    const cuuint64_t dims[4] = {w, 8, kD / w, rows / 8};
    const cuuint64_t strides[3] = {256, 2 * w, 2048};
    const cuuint32_t box[4] = {w, 8, box_cols / w, box_rows / 8};
    const cuuint32_t es[4] = {1, 1, 1, 1};
    enc(m, CU_TENSOR_MAP_DATA_TYPE_BFLOAT16, 4, const_cast<void*>(p), dims, strides, box, es,
        CU_TENSOR_MAP_INTERLEAVE_NONE, w == 64 ? CU_TENSOR_MAP_SWIZZLE_128B : CU_TENSOR_MAP_SWIZZLE_64B,
        box_cols == 128 ? CU_TENSOR_MAP_L2_PROMOTION_L2_256B
                        : box_cols == 64 ? CU_TENSOR_MAP_L2_PROMOTION_L2_128B : CU_TENSOR_MAP_L2_PROMOTION_NONE,
        CU_TENSOR_MAP_FLOAT_OOB_FILL_NONE);
}

}

extern "C" void kernel_launch(void* const* d_in, const int* in_sizes, int n_in, void* d_out, int out_size) {
    (void)in_sizes; (void)n_in; (void)out_size;
    static EncodeFn enc = nullptr;
    if (!enc) {
        cudaDriverEntryPointQueryResult qr;
        cudaGetDriverEntryPoint("cuTensorMapEncodeTiled", (void**)&enc, cudaEnableDefault, &qr);
        cudaFuncSetAttribute(tree_attn_kernel, cudaFuncAttributeMaxDynamicSharedMemorySize, kSmemBytes);
    }
    CUtensorMap tmQ, tmK, tmKt, tmVt, tmV, tmVh, tmVq, tmOh, tmOq;
    make_map(enc, &tmQ, d_in[0], (uint64_t)kCtas * kRows, kRows, 128);
    make_map(enc, &tmK, d_in[1], (uint64_t)kCtas * kC, 32, 128);
    make_map(enc, &tmV, d_in[2], (uint64_t)kCtas * kC, 32, 128);
    make_map(enc, &tmVh, d_in[2], (uint64_t)kCtas * kC, 32, 64);
    make_map(enc, &tmVq, d_in[2], (uint64_t)kCtas * kC, 32, 32);
    make_map(enc, &tmKt, d_in[3], (uint64_t)kCtas * kT, kT, 128);
    make_map(enc, &tmVt, d_in[4], (uint64_t)kCtas * kT, kT, 128);
    make_map(enc, &tmOh, d_out, (uint64_t)kCtas * kRows, 64, 64);
    make_map(enc, &tmOq, d_out, (uint64_t)kCtas * kRows, 64, 32);
    tree_attn_kernel<<<kCtas, kThreads, kSmemBytes, cudaStreamPerThread>>>(
        (const __nv_bfloat16*)d_in[0], tmQ, tmK, tmKt, tmVt, tmV, tmVh, tmVq, tmOh, tmOq,
        (const __nv_bfloat16*)d_in[5], (__nv_bfloat16*)d_out);
}
```
